```python
import torch

def _softmax(x, axis=-1):
    return torch.softmax(x, dim=axis)
def _gelu(x):
    return torch.nn.functional.gelu(x, approximate="tanh")
def _silu(x):
    return torch.nn.functional.silu(x)
def _sigmoid(x):
    return torch.sigmoid(x)
def _layernorm(x, axis=-1, eps=1e-5):
    m = x.mean(dim=axis, keepdim=True)
    v = x.var(dim=axis, keepdim=True, unbiased=False)
    return (x - m) / torch.sqrt(v + eps)
def _scatter_add(tgt, idx, src, axis=0):
    return tgt.clone().index_add_(axis, idx, src)
def _segment_sum(src, seg, n):
    out = torch.zeros((n,) + src.shape[1:], dtype=src.dtype)
    return out.index_add_(0, seg, src)
def _pad(x, pw):
    flat = tuple(v for pair in reversed(pw) for v in pair)
    return torch.nn.functional.pad(x, flat)

kernel_name = 'parallel_sum__sliding_local_dilated__dense_activation_relu__prompt'

def setup_inputs():

    _w = (lambda a: (lambda t: t.to(torch.bfloat16) if t.is_floating_point() else t)(torch.as_tensor(a)))
    def _A_setup():
        B, S, D = 1, 2048, 512
        return {
            "x": _w((lambda *s: torch.randn(*s, dtype=torch.bfloat16) * 0.05)(B, S, D)),
            "wqkv": _w((lambda *s: torch.randn(*s, dtype=torch.bfloat16) * 0.05)(D, 3 * D)),
            "wo": _w((lambda *s: torch.randn(*s, dtype=torch.bfloat16) * 0.05)(D, D)),
        }
    _A_in = _A_setup()

    def _B_setup():
        B, S, D, Dff = 1, 2048, 512, 1376
        return {
            "x": _w((lambda *s: torch.randn(*s, dtype=torch.bfloat16) * 0.05)(B, S, D)),
            "w1": _w((lambda *s: torch.randn(*s, dtype=torch.bfloat16) * 0.05)(D, Dff)),
            "w2": _w((lambda *s: torch.randn(*s, dtype=torch.bfloat16) * 0.05)(Dff, D)),
        }
    _B_in = _B_setup()

    return {
        "A_x": _A_in["x"],
        "A_wqkv": _A_in["wqkv"],
        "A_wo": _A_in["wo"],
        "B_x": _B_in["x"],
        "B_w1": _B_in["w1"],
        "B_w2": _B_in["w2"],
    }

def reference(A_x, A_wqkv, A_wo, B_x, B_w1, B_w2):
    def _A_ref(x, wqkv, wo):
        B, S, D = x.shape
        H = 32; Dh = D // H
        W, dil = 8, 2
        qkv = (lambda x, *d: x.permute(*d))((x @ wqkv).reshape(B, S, 3, H, Dh), 2, 0, 3, 1, 4)
        q, k, v = qkv[0], qkv[1], qkv[2]
        scale = Dh ** -0.5
        pos = torch.arange(S)
        off = torch.arange(W) * dil
        idx = pos[:, None] - off[None, :]
        mask = idx >= 0
        idx_c = torch.where(mask, idx, 0).reshape(-1)
        kg = k[:, :, idx_c, :].reshape(B, H, S, W, Dh)
        vg = v[:, :, idx_c, :].reshape(B, H, S, W, Dh)
        logits = torch.einsum("bhsd,bhswd->bhsw", q, kg) * scale
        logits = torch.where(mask[None, None, :, :], logits, -1e9)
        attn = _softmax(logits, axis=-1)
        o = torch.einsum("bhsw,bhswd->bhsd", attn, vg)
        return (lambda x, *d: x.permute(*d))(o, 0, 2, 1, 3).reshape(B, S, D) @ wo

    def _B_ref(x, w1, w2):
        h = torch.einsum("bsd,df->bsf", x, w1)
        zero = torch.zeros_like(h)
        h = torch.maximum(h, zero)
        return torch.einsum("bsf,fd->bsd", h, w2)

    x = A_x
    xn = _layernorm(x, axis=-1)
    return x + _A_ref(xn, A_wqkv, A_wo) + _B_ref(xn, B_w1, B_w2)
```

```cpp
#include <cuda_runtime.h>
#include <cuda_bf16.h>
#include <cuda.h>
#include <stdint.h>
#include <type_traits>

namespace {

constexpr int kS = 2048, kD = 512, kF = 1376;
constexpr int kFS = 176;
constexpr int kCS = 192 + kFS;
constexpr int RING = 10;
constexpr int NSLOT = 80;
constexpr int LAG = 2;

constexpr uint32_t OFF_U = 0;
constexpr uint32_t OFF_RING = 8 * 16384;
constexpr uint32_t OFF_HALO = OFF_RING + RING * 8192;
constexpr uint32_t OFF_CS = OFF_HALO + 4096;
constexpr uint32_t OFF_BAR = OFF_CS + 1536;
constexpr int B_FULL = 0, B_EMPTY = B_FULL + RING, B_X = B_EMPTY + RING  , B_LAND = B_X + 16  ,
              B_QKV = B_LAND + 8, B_O = B_QKV + 1, B_CS = B_O + 1, B_PEERX = B_CS + 1, B_PW = B_PEERX + 1  ,
              B_PR = B_PW + 6  , B_RES = B_PR + 2  , B_HALO = B_RES + 2, B_COUNT = B_HALO + 1;
constexpr uint32_t SMEM_USED = OFF_BAR + B_COUNT * 8;
constexpr uint32_t SMEM_BYTES = SMEM_USED + 1024;

constexpr int SPIN_LIMIT = 1 << 22;

__device__ float g_cs_part[8 * 16 * kCS];
__device__ uint32_t g_cs_flag[8 * 32];
__device__ uint4 g_halo[16 * 8 * 256];
__device__ uint32_t g_halo_flag[16 * 8 * 8];
__device__ uint4 g_part[16 * 2 * 4 * 4 * 2 * 512];
__device__ uint32_t g_part_flag[16 * 2 * 4 * 8];
__device__ uint32_t g_launch_cnt[128];

__device__ __forceinline__ uint32_t smem_u32(const void* p) { return (uint32_t)__cvta_generic_to_shared(p); }
__device__ __forceinline__ void mbar_init(uint32_t bar, uint32_t count) {
  asm volatile("mbarrier.init.shared::cta.b64 [%0], %1;" ::"r"(bar), "r"(count));
}
__device__ __forceinline__ void mbar_expect_tx(uint32_t bar, uint32_t bytes) {
  asm volatile("mbarrier.arrive.expect_tx.shared::cta.b64 _, [%0], %1;" ::"r"(bar), "r"(bytes) : "memory");
}
__device__ __forceinline__ void mbar_arrive(uint32_t bar) {
  asm volatile("mbarrier.arrive.shared::cta.b64 _, [%0];" ::"r"(bar) : "memory");
}
__device__ __forceinline__ void mbar_arrive_remote(uint32_t bar_cluster) {
  asm volatile("mbarrier.arrive.shared::cluster.b64 _, [%0];" ::"r"(bar_cluster) : "memory");
}
__device__ __forceinline__ void mbar_wait(uint32_t bar, uint32_t parity) {
  asm volatile("{\n.reg .pred p, q;\n.reg .u32 c;\nmov.u32 c, 0;\n"
               "WAIT_LOOP:\nmbarrier.try_wait.parity.shared::cta.b64 p, [%0], %1;\n@p bra WAIT_DONE;\n"
               "add.u32 c, c, 1;\nsetp.gt.u32 q, c, %2;\n@q trap;\nbra WAIT_LOOP;\nWAIT_DONE:\n}\n"
               ::"r"(bar), "r"(parity), "n"(SPIN_LIMIT) : "memory");
}
__device__ __forceinline__ void mbar_wait_cluster(uint32_t bar, uint32_t parity) {
  asm volatile("{\n.reg .pred p, q;\n.reg .u32 c;\nmov.u32 c, 0;\n"
               "WAIT_LOOP:\nmbarrier.try_wait.parity.acquire.cluster.shared::cta.b64 p, [%0], %1;\n@p bra WAIT_DONE;\n"
               "add.u32 c, c, 1;\nsetp.gt.u32 q, c, %2;\n@q trap;\nbra WAIT_LOOP;\nWAIT_DONE:\n}\n"
               ::"r"(bar), "r"(parity), "n"(SPIN_LIMIT) : "memory");
}
__device__ __forceinline__ bool elect_one() {
  uint32_t pred;
  asm volatile("{\n.reg .pred p;\nelect.sync _|p, 0xffffffff;\nselp.u32 %0, 1, 0, p;\n}\n" : "=r"(pred));
  return pred;
}
__device__ __forceinline__ void tma_load(uint32_t dst, const CUtensorMap* tm, uint32_t bar, int c0, int c1) {
  asm volatile("cp.async.bulk.tensor.2d.shared::cluster.global.mbarrier::complete_tx::bytes [%0], [%1, {%3, %4}], [%2];"
               ::"r"(dst), "l"(tm), "r"(bar), "r"(c0), "r"(c1) : "memory");
}
__device__ __forceinline__ void tma_prefetch(const CUtensorMap* tm, int c0, int c1) {
  asm volatile("cp.async.bulk.prefetch.tensor.2d.L2.global [%0, {%1, %2}];" ::"l"(tm), "r"(c0), "r"(c1) : "memory");
}
__device__ __forceinline__ void tma_store(const CUtensorMap* tm, uint32_t src, int c0, int c1) {
  asm volatile("cp.async.bulk.tensor.2d.global.shared::cta.bulk_group [%0, {%2, %3}], [%1];"
               ::"l"(tm), "r"(src), "r"(c0), "r"(c1) : "memory");
}
__device__ __forceinline__ void prefetch_tmap(const CUtensorMap* tm) {
  asm volatile("prefetch.tensormap [%0];" ::"l"(tm) : "memory");
}
__device__ __forceinline__ uint32_t mapa(uint32_t addr, uint32_t rank) {
  uint32_t r;
  asm("mapa.shared::cluster.u32 %0, %1, %2;" : "=r"(r) : "r"(addr), "r"(rank));
  return r;
}
__device__ __forceinline__ void st_async4(uint32_t addr, uint32_t bar, uint32_t a, uint32_t b, uint32_t c, uint32_t d) {
  asm volatile("st.async.weak.shared::cluster.mbarrier::complete_tx::bytes.v4.b32 [%0], {%2, %3, %4, %5}, [%1];"
               ::"r"(addr), "r"(bar), "r"(a), "r"(b), "r"(c), "r"(d) : "memory");
}
__device__ __forceinline__ void ldsm4(uint32_t addr, uint32_t& a, uint32_t& b, uint32_t& c, uint32_t& d) {
  asm volatile("ldmatrix.sync.aligned.m8n8.x4.shared.b16 {%0, %1, %2, %3}, [%4];"
               : "=r"(a), "=r"(b), "=r"(c), "=r"(d) : "r"(addr) : "memory");
}
__device__ __forceinline__ void ldsm2(uint32_t addr, uint32_t& a, uint32_t& b) {
  asm volatile("ldmatrix.sync.aligned.m8n8.x2.shared.b16 {%0, %1}, [%2];" : "=r"(a), "=r"(b) : "r"(addr) : "memory");
}
__device__ __forceinline__ void ldsm4t(uint32_t addr, uint32_t& a, uint32_t& b, uint32_t& c, uint32_t& d) {
  asm volatile("ldmatrix.sync.aligned.m8n8.x4.trans.shared.b16 {%0, %1, %2, %3}, [%4];"
               : "=r"(a), "=r"(b), "=r"(c), "=r"(d) : "r"(addr) : "memory");
}
__device__ __forceinline__ void ldsm2t(uint32_t addr, uint32_t& a, uint32_t& b) {
  asm volatile("ldmatrix.sync.aligned.m8n8.x2.trans.shared.b16 {%0, %1}, [%2];" : "=r"(a), "=r"(b) : "r"(addr) : "memory");
}
__device__ __forceinline__ void stsm4(uint32_t addr, uint32_t a, uint32_t b, uint32_t c, uint32_t d) {
  asm volatile("stmatrix.sync.aligned.m8n8.x4.shared.b16 [%0], {%1, %2, %3, %4};"
               ::"r"(addr), "r"(a), "r"(b), "r"(c), "r"(d) : "memory");
}
__device__ __forceinline__ void lds128(uint32_t addr, uint32_t& a, uint32_t& b, uint32_t& c, uint32_t& d) {
  asm volatile("ld.shared.v4.b32 {%0, %1, %2, %3}, [%4];" : "=r"(a), "=r"(b), "=r"(c), "=r"(d) : "r"(addr) : "memory");
}
__device__ __forceinline__ void sts128(uint32_t addr, uint32_t a, uint32_t b, uint32_t c, uint32_t d) {
  asm volatile("st.shared.v4.b32 [%0], {%1, %2, %3, %4};" ::"r"(addr), "r"(a), "r"(b), "r"(c), "r"(d) : "memory");
}
__device__ __forceinline__ float2 lds64f(uint32_t addr) {
  float2 v;
  asm volatile("ld.shared.v2.f32 {%0, %1}, [%2];" : "=f"(v.x), "=f"(v.y) : "r"(addr) : "memory");
  return v;
}
__device__ __forceinline__ uint32_t pack_bf16(float lo, float hi) {
  uint32_t r;
  asm("cvt.rn.bf16x2.f32 %0, %1, %2;" : "=r"(r) : "f"(hi), "f"(lo));
  return r;
}
__device__ __forceinline__ uint32_t pack_bf16_relu(float lo, float hi) {
  uint32_t r;
  asm("cvt.rn.relu.bf16x2.f32 %0, %1, %2;" : "=r"(r) : "f"(hi), "f"(lo));
  return r;
}
__device__ __forceinline__ float bf_lo(uint32_t v) { return __uint_as_float(v << 16); }
__device__ __forceinline__ float bf_hi(uint32_t v) { return __uint_as_float(v & 0xffff0000u); }
__device__ __forceinline__ void publish_flag(uint32_t* p, uint32_t v) {
  asm volatile("fence.acq_rel.gpu;\nst.relaxed.gpu.global.u32 [%0], %1;" ::"l"(p), "r"(v) : "memory");
}
__device__ __forceinline__ void poll_flag(const uint32_t* ptr, uint32_t e) {
  asm volatile("{\n.reg .pred p, q;\n.reg .u32 c, v;\nmov.u32 c, 0;\n"
               "POLL_LOOP:\nld.acquire.gpu.global.u32 v, [%0];\nsetp.eq.u32 p, v, %1;\n@p bra POLL_DONE;\n"
               "add.u32 c, c, 1;\nsetp.gt.u32 q, c, %2;\n@q trap;\nbra POLL_LOOP;\nPOLL_DONE:\n}\n"
               ::"l"(ptr), "r"(e), "n"(SPIN_LIMIT) : "memory");
}
__device__ __forceinline__ uint4 ldg_cg(const uint4* p) {
  uint4 v;
  asm volatile("ld.global.cg.v4.u32 {%0, %1, %2, %3}, [%4];" : "=r"(v.x), "=r"(v.y), "=r"(v.z), "=r"(v.w) : "l"(p) : "memory");
  return v;
}
__device__ __forceinline__ void bar_sync(int id, int n) { asm volatile("bar.sync %0, %1;" ::"r"(id), "r"(n) : "memory"); }
__device__ __forceinline__ void wg_fence() { asm volatile("wgmma.fence.sync.aligned;" ::: "memory"); }
__device__ __forceinline__ void wg_commit() { asm volatile("wgmma.commit_group.sync.aligned;" ::: "memory"); }
template <int N> __device__ __forceinline__ void wg_wait() { asm volatile("wgmma.wait_group.sync.aligned %0;" ::"n"(N) : "memory"); }
__device__ __forceinline__ void fence_acc(float (&d)[32]) {
#pragma unroll
  for (int i = 0; i < 32; i++) asm volatile("" : "+f"(d[i])::"memory");
}
__device__ __forceinline__ uint32_t b_desc_lo(uint32_t saddr) { return ((saddr & 0x3FFFF) >> 4) | ((8192u >> 4) << 16); }
__device__ __forceinline__ void mma16816(float (&c)[4], uint32_t a0, uint32_t a1, uint32_t a2, uint32_t a3, uint32_t b0, uint32_t b1) {
  asm volatile("mma.sync.aligned.m16n8k16.row.col.f32.bf16.bf16.f32 {%0, %1, %2, %3}, {%4, %5, %6, %7}, {%8, %9}, {%0, %1, %2, %3};"
               : "+f"(c[0]), "+f"(c[1]), "+f"(c[2]), "+f"(c[3]) : "r"(a0), "r"(a1), "r"(a2), "r"(a3), "r"(b0), "r"(b1));
}
__device__ __forceinline__ void mma1688(float (&c)[4], uint32_t a0, uint32_t a1, uint32_t b0) {
  asm volatile("mma.sync.aligned.m16n8k8.row.col.f32.bf16.bf16.f32 {%0, %1, %2, %3}, {%4, %5}, {%6}, {%0, %1, %2, %3};"
               : "+f"(c[0]), "+f"(c[1]), "+f"(c[2]), "+f"(c[3]) : "r"(a0), "r"(a1), "r"(b0));
}

template <int OFF, int SCALE_D>
__device__ __forceinline__ void wgmma_rs_n64(float (&d)[32], uint32_t a0, uint32_t a1, uint32_t a2, uint32_t a3, uint32_t desc_lo) {
  asm volatile("{\n.reg .pred p;\n.reg .b32 lo;\n.reg .b64 db;\nadd.u32 lo, %36, %37;\nmov.b64 db, {lo, 0x40000040};\n"
    "setp.ne.b32 p, %38, 0;\n"
    "wgmma.mma_async.sync.aligned.m64n64k16.f32.bf16.bf16 "
    "{%0, %1, %2, %3, %4, %5, %6, %7, %8, %9, %10, %11, %12, %13, %14, %15, %16, %17, %18, %19, %20, %21, %22, %23, %24, %25, %26, %27, %28, %29, %30, %31}, "
    "{%32,%33,%34,%35}, db, p, 1, 1, 1;\n}\n"
    : "+f"(d[0]), "+f"(d[1]), "+f"(d[2]), "+f"(d[3]), "+f"(d[4]), "+f"(d[5]), "+f"(d[6]), "+f"(d[7]), "+f"(d[8]), "+f"(d[9]), "+f"(d[10]), "+f"(d[11]), "+f"(d[12]), "+f"(d[13]), "+f"(d[14]), "+f"(d[15]), "+f"(d[16]), "+f"(d[17]), "+f"(d[18]), "+f"(d[19]), "+f"(d[20]), "+f"(d[21]), "+f"(d[22]), "+f"(d[23]), "+f"(d[24]), "+f"(d[25]), "+f"(d[26]), "+f"(d[27]), "+f"(d[28]), "+f"(d[29]), "+f"(d[30]), "+f"(d[31])
    : "r"(a0), "r"(a1), "r"(a2), "r"(a3), "r"(desc_lo), "n"(OFF), "n"(SCALE_D));
}
template <int OFF, int SCALE_D>
__device__ __forceinline__ void wgmma_rs_n48(float (&d)[32], uint32_t a0, uint32_t a1, uint32_t a2, uint32_t a3, uint32_t desc_lo) {
  asm volatile("{\n.reg .pred p;\n.reg .b32 lo;\n.reg .b64 db;\nadd.u32 lo, %28, %29;\nmov.b64 db, {lo, 0x40000040};\n"
    "setp.ne.b32 p, %30, 0;\n"
    "wgmma.mma_async.sync.aligned.m64n48k16.f32.bf16.bf16 "
    "{%0, %1, %2, %3, %4, %5, %6, %7, %8, %9, %10, %11, %12, %13, %14, %15, %16, %17, %18, %19, %20, %21, %22, %23}, "
    "{%24,%25,%26,%27}, db, p, 1, 1, 1;\n}\n"
    : "+f"(d[0]), "+f"(d[1]), "+f"(d[2]), "+f"(d[3]), "+f"(d[4]), "+f"(d[5]), "+f"(d[6]), "+f"(d[7]), "+f"(d[8]), "+f"(d[9]), "+f"(d[10]), "+f"(d[11]), "+f"(d[12]), "+f"(d[13]), "+f"(d[14]), "+f"(d[15]), "+f"(d[16]), "+f"(d[17]), "+f"(d[18]), "+f"(d[19]), "+f"(d[20]), "+f"(d[21]), "+f"(d[22]), "+f"(d[23])
    : "r"(a0), "r"(a1), "r"(a2), "r"(a3), "r"(desc_lo), "n"(OFF), "n"(SCALE_D));
}

#define TSTAMP(idx) do {} while (0)

struct Params {
  const __nv_bfloat16* wqkv;
  const __nv_bfloat16* w1;
};

template <int n, int AOFF, int NKS, bool FIRST, bool N48>
__device__ __forceinline__ void issue_tile(float (&acc)[32], const uint32_t (&A)[128], uint32_t sb, uint32_t ring_desc) {
  constexpr int s = n % RING;
  mbar_wait(sb + OFF_BAR + (B_FULL + s) * 8, (n / RING) & 1);
  wg_fence();
  auto step = [&](auto KS) {
    constexpr int ks = decltype(KS)::value;
    if constexpr (ks < NKS) {
      constexpr int off = (s * 8192 + ks * 2048) >> 4;
      constexpr int sc = (FIRST && ks == 0) ? 0 : 1;
      if constexpr (N48) wgmma_rs_n48<off, sc>(acc, A[AOFF + 4 * ks], A[AOFF + 4 * ks + 1], A[AOFF + 4 * ks + 2], A[AOFF + 4 * ks + 3], ring_desc);
      else wgmma_rs_n64<off, sc>(acc, A[AOFF + 4 * ks], A[AOFF + 4 * ks + 1], A[AOFF + 4 * ks + 2], A[AOFF + 4 * ks + 3], ring_desc);
    }
  };
  step(std::integral_constant<int, 0>{}); step(std::integral_constant<int, 1>{});
  step(std::integral_constant<int, 2>{}); step(std::integral_constant<int, 3>{});
  wg_commit();
}
template <int n, int L>
__device__ __forceinline__ void retire(uint32_t sb, int lane) {
  wg_wait<L>();
  if (n - L >= 0 && n - L + RING < NSLOT) {
    if (lane == 0) mbar_arrive(sb + OFF_BAR + (B_EMPTY + (n - L) % RING) * 8);
  }
}
template <int s_from, int s_to>
__device__ __forceinline__ void release_range(uint32_t sb, int lane) {
#pragma unroll
  for (int t = s_from; t < s_to; t++)
    if (t >= 0 && t + RING < NSLOT) {
      if (lane == 0) mbar_arrive(sb + OFF_BAR + (B_EMPTY + t % RING) * 8);
    }
}

struct RowStats { float mean0, mean1, r0, r1; };

template <bool RELU>
__device__ __forceinline__ void epi16(const float (&acc)[32], int g, uint32_t cs_addr, const RowStats& st, float r0, float r1,
                                      uint32_t& p0, uint32_t& p1, uint32_t& p2, uint32_t& p3) {
  const float2 c0 = lds64f(cs_addr + (16 * g) * 4);
  const float2 c1 = lds64f(cs_addr + (16 * g + 8) * 4);
  const float y0 = fmaf(-st.mean0, c0.x, acc[8 * g + 0]) * r0, y1 = fmaf(-st.mean0, c0.y, acc[8 * g + 1]) * r0;
  const float y2 = fmaf(-st.mean1, c0.x, acc[8 * g + 2]) * r1, y3 = fmaf(-st.mean1, c0.y, acc[8 * g + 3]) * r1;
  const float y4 = fmaf(-st.mean0, c1.x, acc[8 * g + 4]) * r0, y5 = fmaf(-st.mean0, c1.y, acc[8 * g + 5]) * r0;
  const float y6 = fmaf(-st.mean1, c1.x, acc[8 * g + 6]) * r1, y7 = fmaf(-st.mean1, c1.y, acc[8 * g + 7]) * r1;
  if (RELU) { p0 = pack_bf16_relu(y0, y1); p1 = pack_bf16_relu(y2, y3); p2 = pack_bf16_relu(y4, y5); p3 = pack_bf16_relu(y6, y7); }
  else { p0 = pack_bf16(y0, y1); p1 = pack_bf16(y2, y3); p2 = pack_bf16(y4, y5); p3 = pack_bf16(y6, y7); }
}

__device__ __forceinline__ uint32_t frag_addr(uint32_t tile_row0_addr, int lane, int g) {
  const int r = (lane & 7) + (lane & 8);
  const int chunk = 2 * g + (lane >> 4);
  return tile_row0_addr + r * 128 + ((chunk ^ (lane & 7)) << 4);
}

__global__ void __cluster_dims__(2, 1, 1) __launch_bounds__(384, 1)
fused_kernel(const __grid_constant__ CUtensorMap tmX, const __grid_constant__ CUtensorMap tmWqkv,
             const __grid_constant__ CUtensorMap tmW1, const __grid_constant__ CUtensorMap tmWo,
             const __grid_constant__ CUtensorMap tmW2, const __grid_constant__ CUtensorMap tmOut, Params prm) {
  extern __shared__ uint8_t smem_raw[];
  const uint32_t sb = (smem_u32(smem_raw) + 1023u) & ~1023u;
  const int warp = __shfl_sync(0xffffffffu, threadIdx.x >> 5, 0);
  const int lane = threadIdx.x & 31;
  const int ti = blockIdx.x >> 3;
  const int tj = blockIdx.x & 7;
  const int ta = tj >> 1, tb = tj & 1;

  if (threadIdx.x == 0) {
    for (int s = 0; s < RING; s++) { mbar_init(sb + OFF_BAR + (B_FULL + s) * 8, 1); mbar_init(sb + OFF_BAR + (B_EMPTY + s) * 8, 8); }
    for (int s = 0; s < 16; s++) mbar_init(sb + OFF_BAR + (B_X + s) * 8, 1);
    for (int s = 0; s < 8; s++) mbar_init(sb + OFF_BAR + (B_LAND + s) * 8, 1);
    mbar_init(sb + OFF_BAR + B_QKV * 8, 8);
    mbar_init(sb + OFF_BAR + B_O * 8, 3);
    mbar_init(sb + OFF_BAR + B_CS * 8, 3);
    mbar_init(sb + OFF_BAR + B_PEERX * 8, 8);
    for (int s = 0; s < 6; s++) mbar_init(sb + OFF_BAR + (B_PW + s) * 8, 4);
    for (int s = 0; s < 2; s++) { mbar_init(sb + OFF_BAR + (B_PR + s) * 8, 1); mbar_init(sb + OFF_BAR + (B_RES + s) * 8, 1); }
    mbar_init(sb + OFF_BAR + B_HALO * 8, 1);
    for (int t = 0; t < 4; t++)
      for (int p = 0; p < 2; p++) mbar_expect_tx(sb + OFF_BAR + (B_LAND + 2 * t + p) * 8, t == 3 ? 6144 : 8192);
    asm volatile("fence.mbarrier_init.release.cluster;" ::: "memory");
  }
  __syncthreads();
  asm volatile("barrier.cluster.arrive.relaxed.aligned;" ::: "memory");

  if (warp >= 8) {
    asm volatile("setmaxnreg.dec.sync.aligned.u32 56;");
    if (warp == 8) {
      TSTAMP(0);
      if (elect_one()) {
        prefetch_tmap(&tmX); prefetch_tmap(&tmWqkv); prefetch_tmap(&tmW1); prefetch_tmap(&tmWo); prefetch_tmap(&tmW2); prefetch_tmap(&tmOut);
      }
      __syncwarp();
      auto load_slot = [&](int n) {
        const int s = n % RING;
        const uint32_t bar = sb + OFF_BAR + (B_FULL + s) * 8, dst = sb + OFF_RING + s * 8192;
        const CUtensorMap* tm; int c0, c1;
        if (n < 16) { tm = &tmWqkv; c0 = 512 * (n & 1) + 64 * tj; c1 = 64 * (n >> 1); }
        else if (n < 24) { tm = &tmWqkv; c0 = 1024 + 64 * tj; c1 = 64 * (n - 16); }
        else if (n < 48) { tm = &tmW1; c0 = kFS * tj + 64 * ((n - 24) >> 3); c1 = 64 * ((n - 24) & 7); }
        else {
          const int blk = (n - 48) >> 3, t = (n - 48) & 7;
          c0 = 256 * tb + 64 * ((ta + 1 + blk) & 3);
          const int jj = (t == 3 || t == 4 || t == 5 || t == 7) ? (tj ^ 1) : tj;
          if (t == 0 || t == 3) { tm = &tmWo; c1 = 64 * jj; }
          else { tm = &tmW2; c1 = kFS * jj + (t >= 6 ? 128 : ((t == 2 || t == 5) ? 64 : 0)); }
        }
        if (elect_one()) { mbar_expect_tx(bar, 8192); tma_load(dst, tm, bar, c0, c1); }
        __syncwarp();
      };
      auto load_x = [&](int kb) {
        if (elect_one()) {
#pragma unroll
          for (int p = 0; p < 2; p++) {
            const uint32_t bar = sb + OFF_BAR + (B_X + 2 * kb + p) * 8;
            mbar_expect_tx(bar, 8192);
            tma_load(sb + OFF_U + kb * 16384 + p * 8192, &tmX, bar, 512 * p + 64 * kb, 64 * ti);
          }
        }
        __syncwarp();
      };
      for (int kb = 0; kb < RING / 2; kb++) { load_x(kb); load_slot(2 * kb); load_slot(2 * kb + 1); }
      for (int kb = RING / 2; kb < 8; kb++) load_x(kb);
      if (elect_one()) {
#pragma unroll
        for (int u = 0; u < 2; u++) {
          const int m = 2 * ti + u;
          if (m < 8) tma_prefetch(&tmWqkv, 1024 + 64 * tj, 64 * m);
          else tma_prefetch(&tmW1, kFS * tj + 64 * ((m - 8) >> 3), 64 * ((m - 8) & 7));
          const int blk = m >> 3, t = m & 7;
          const int c0 = 256 * tb + 64 * blk;
          const int jj = (t == 3 || t == 4 || t == 5 || t == 7) ? (tj ^ 1) : tj;
          if (t == 0 || t == 3) tma_prefetch(&tmWo, c0, 64 * jj);
          else tma_prefetch(&tmW2, c0, kFS * jj + (t >= 6 ? 128 : ((t == 2 || t == 5) ? 64 : 0)));
        }
      }
      __syncwarp();
      for (int n = RING; n < NSLOT; n++) {
        mbar_wait(sb + OFF_BAR + (B_EMPTY + n % RING) * 8, ((n / RING) - 1) & 1);
        load_slot(n);
        if (n == 60) {
          mbar_wait(sb + OFF_BAR + B_O * 8, 0);
          if (elect_one()) {
            asm volatile("fence.proxy.async.shared::cta;" ::: "memory");
#pragma unroll
            for (int p = 0; p < 2; p++) {
              const uint32_t bar = sb + OFF_BAR + (B_RES + p) * 8;
              mbar_expect_tx(bar, 8192);
              tma_load(sb + OFF_U + 16384 + p * 8192, &tmX, bar, 512 * p + 256 * tb + 64 * ta, 64 * ti);
            }
          }
          __syncwarp();
        }
      }
      TSTAMP(1);
    } else {
      const int hw = warp - 9, ht = threadIdx.x - 288;
      const uint32_t epoch = g_launch_cnt[blockIdx.x] + 1;
      {
        float s0 = 0.f, s1 = 0.f, s2 = 0.f, s3 = 0.f;
        if (ht < kCS / 4) {
          const __nv_bfloat16* src; int pitch; bool ok = true;
          if (ht < 48) { src = prm.wqkv + 512 * (ht >> 4) + 64 * tj + 4 * (ht & 15); pitch = 1536; }
          else { const int c = kFS * tj + 4 * (ht - 48); src = prm.w1 + c; pitch = kF; ok = c < kF; }
          if (ok) {
            src += (size_t)(32 * ti) * pitch;
#pragma unroll 16
            for (int k = 0; k < 32; k++) {
              const uint2 v = __ldg(reinterpret_cast<const uint2*>(src + (size_t)k * pitch));
              s0 += bf_lo(v.x); s1 += bf_hi(v.x); s2 += bf_lo(v.y); s3 += bf_hi(v.y);
            }
          }
          *reinterpret_cast<float4*>(&g_cs_part[(tj * 16 + ti) * kCS + 4 * ht]) = make_float4(s0, s1, s2, s3);
        }
        bar_sync(3, 96);
        if (ht == 0) { g_launch_cnt[blockIdx.x] = epoch; publish_flag(&g_cs_flag[tj * 32 + ti], epoch); }
        if (hw == 0) { if (lane < 16) poll_flag(&g_cs_flag[tj * 32 + lane], epoch); __syncwarp(); }
        bar_sync(3, 96);
        if (ht < kCS / 4) {
          float4 t = make_float4(0.f, 0.f, 0.f, 0.f);
#pragma unroll
          for (int ii = 0; ii < 16; ii++) {
            const uint4 v = ldg_cg(reinterpret_cast<const uint4*>(&g_cs_part[(tj * 16 + ii) * kCS + 4 * ht]));
            t.x += __uint_as_float(v.x); t.y += __uint_as_float(v.y); t.z += __uint_as_float(v.z); t.w += __uint_as_float(v.w);
          }
          sts128(sb + OFF_CS + ht * 16, __float_as_uint(t.x), __float_as_uint(t.y), __float_as_uint(t.z), __float_as_uint(t.w));
        }
        __syncwarp();
        if (lane == 0) mbar_arrive(sb + OFF_BAR + B_CS * 8);
        TSTAMP(2 + hw);
      }
      const uint32_t Qt = sb + OFF_U, Kt = sb + OFF_U + 16384, Vt = sb + OFF_U + 32768;
      const uint32_t Hk = sb + OFF_HALO, Hv = sb + OFF_HALO + 2048;
      mbar_wait(sb + OFF_BAR + B_QKV * 8, 0);
      TSTAMP(5 + hw);
      if (hw == 2) {
        if (ti < 15) {
          uint4* dst = &g_halo[(ti * 8 + tj) * 256];
#pragma unroll
          for (int u = 0; u < 4; u++) {
            const uint32_t src = (u < 2 ? Kt : Vt) + (u & 1) * 8192 + 56 * 128;
#pragma unroll
            for (int v = 0; v < 2; v++) {
              uint32_t a, b, c, d;
              lds128(src + (v * 32 + lane) * 16, a, b, c, d);
              dst[u * 64 + v * 32 + lane] = make_uint4(a, b, c, d);
            }
          }
          __syncwarp();
          if (lane == 0) publish_flag(&g_halo_flag[(ti * 8 + tj) * 8], epoch);
        }
      }
      const int g = lane >> 2, q = lane & 3;
      auto attn_unit = [&](const int p, const int blk) {
        const uint32_t r0 = 64 * p + 16 * blk;
        const bool halo = (blk == 0);
        const bool first = halo && (ti == 0);
        const int m = lane >> 3, rr = lane & 7;
        uint32_t kA = (m < 2 && halo) ? (Hk + p * 1024 + rr * 128) : (Kt + (r0 - 8 + 8 * (m >> 1) + rr) * 128);
        uint32_t kB = Kt + (r0 + 8 + rr) * 128;
        const int kc = m & 1;
        uint32_t vA = ((m & 1) == 0 && halo) ? (Hv + p * 1024 + rr * 128) : (Vt + (r0 - 8 + 8 * (m & 1) + rr) * 128);
        uint32_t vB = Vt + (r0 + 8 + rr) * 128;
        const int vc = m >> 1;
        const uint32_t qA = Qt + (r0 + (lane & 15)) * 128;
        const int qc = lane >> 4;
#pragma unroll
        for (int h = 0; h < 4; h++) {
          uint32_t q0, q1, q2, q3, k0, k1, k2, k3, k4, k5, v0, v1, v2, v3, v4, v5;
          const uint32_t qaddr = qA + (((2 * h + qc) ^ rr) << 4);
          ldsm4(qaddr, q0, q1, q2, q3);
          ldsm4(kA + (((2 * h + kc) ^ rr) << 4), k0, k1, k2, k3);
          ldsm2(kB + (((2 * h + kc) ^ rr) << 4), k4, k5);
          ldsm4t(vA + (((2 * h + vc) ^ rr) << 4), v0, v1, v2, v3);
          ldsm2t(vB + (((2 * h + (m & 1)) ^ rr) << 4), v4, v5);
          float s0[4] = {0.f, 0.f, 0.f, 0.f}, s1[4] = {0.f, 0.f, 0.f, 0.f}, s2[4] = {0.f, 0.f, 0.f, 0.f};
          mma16816(s0, q0, q1, q2, q3, k0, k1);
          mma16816(s1, q0, q1, q2, q3, k2, k3);
          mma16816(s2, q0, q1, q2, q3, k4, k5);
          const bool u0 = (2 * q) <= g, u1 = (2 * q + 1) <= g;
          const float NEG = -INFINITY;
          const float a0 = u0 ? s1[0] : (first ? NEG : s0[0]), a1 = u1 ? s1[1] : (first ? NEG : s0[1]);
          const float b0 = u0 ? s2[2] : s1[2], b1 = u1 ? s2[3] : s1[3];
          float ma = fmaxf(a0, a1), mb = fmaxf(b0, b1);
          ma = fmaxf(ma, __shfl_xor_sync(0xffffffffu, ma, 1)); mb = fmaxf(mb, __shfl_xor_sync(0xffffffffu, mb, 1));
          ma = fmaxf(ma, __shfl_xor_sync(0xffffffffu, ma, 2)); mb = fmaxf(mb, __shfl_xor_sync(0xffffffffu, mb, 2));
          constexpr float LOG2E = 1.4426950408889634f;
          const float ea0 = exp2f((a0 - ma) * LOG2E), ea1 = exp2f((a1 - ma) * LOG2E);
          const float eb0 = exp2f((b0 - mb) * LOG2E), eb1 = exp2f((b1 - mb) * LOG2E);
          float sa = ea0 + ea1, sb2 = eb0 + eb1;
          sa += __shfl_xor_sync(0xffffffffu, sa, 1); sb2 += __shfl_xor_sync(0xffffffffu, sb2, 1);
          sa += __shfl_xor_sync(0xffffffffu, sa, 2); sb2 += __shfl_xor_sync(0xffffffffu, sb2, 2);
          const float ia = __fdividef(1.f, sa), ib = __fdividef(1.f, sb2);
          const float pa0 = ea0 * ia, pa1 = ea1 * ia, pb0 = eb0 * ib, pb1 = eb1 * ib;
          const uint32_t P0 = pack_bf16(u0 ? 0.f : pa0, u1 ? 0.f : pa1);
          const uint32_t P2 = pack_bf16(u0 ? pa0 : 0.f, u1 ? pa1 : 0.f);
          const uint32_t P3 = pack_bf16(u0 ? 0.f : pb0, u1 ? 0.f : pb1);
          const uint32_t P5 = pack_bf16(u0 ? pb0 : 0.f, u1 ? pb1 : 0.f);
          float o0[4] = {0.f, 0.f, 0.f, 0.f}, o1[4] = {0.f, 0.f, 0.f, 0.f};
          mma16816(o0, P0, 0u, P2, P3, v0, v1);
          mma16816(o1, P0, 0u, P2, P3, v2, v3);
          mma1688(o0, 0u, P5, v4);
          mma1688(o1, 0u, P5, v5);
          stsm4(qaddr, pack_bf16(o0[0], o0[1]), pack_bf16(o0[2], o0[3]), pack_bf16(o1[0], o1[1]), pack_bf16(o1[2], o1[3]));
        }
      };
      attn_unit(hw >= 2 ? 1 : 0, hw == 0 ? 1 : (hw == 1 ? 2 : 1));
      if (hw == 2) {
        if (ti > 0) {
          if (lane == 0) poll_flag(&g_halo_flag[((ti - 1) * 8 + tj) * 8], epoch);
          __syncwarp();
          const uint4* src = &g_halo[((ti - 1) * 8 + tj) * 256];
#pragma unroll
          for (int v = 0; v < 8; v++) { const uint4 t = ldg_cg(src + v * 32 + lane); sts128(sb + OFF_HALO + (v * 32 + lane) * 16, t.x, t.y, t.z, t.w); }
        } else {
#pragma unroll
          for (int v = 0; v < 8; v++) sts128(sb + OFF_HALO + (v * 32 + lane) * 16, 0u, 0u, 0u, 0u);
        }
        __syncwarp();
        if (lane == 0) mbar_arrive(sb + OFF_BAR + B_HALO * 8);
      }
      attn_unit(hw == 0 ? 0 : 1, hw == 0 ? 3 : (hw == 1 ? 2 : 3));
      if (hw < 2) {
        mbar_wait(sb + OFF_BAR + B_HALO * 8, 0);
        attn_unit(hw, 0);
      }
      __syncwarp();
      if (lane == 0) mbar_arrive(sb + OFF_BAR + B_O * 8);
      TSTAMP(8 + hw);
      if (hw < 2) {
#pragma unroll 1
        for (int blk = 0; blk < 3; blk++) {
          mbar_wait(sb + OFF_BAR + (B_PW + 2 * blk + hw) * 8, 0);
          const int c = (ta + 1 + blk) & 3;
          if (lane == 0) publish_flag(&g_part_flag[(((ti * 2 + tb) * 4 + c) * 2 + hw) * 4 + ta], epoch);
          __syncwarp();
        }
        if (lane < 4 && lane != ta) poll_flag(&g_part_flag[(((ti * 2 + tb) * 4 + ta) * 2 + hw) * 4 + lane], epoch);
        __syncwarp();
        if (lane == 0) mbar_arrive(sb + OFF_BAR + (B_PR + hw) * 8);
        TSTAMP(11 + hw);
      }
    }
  } else {
    asm volatile("setmaxnreg.inc.sync.aligned.u32 224;");
    const int p = warp >> 2;
    const int wq = warp & 3;
    const int tw = threadIdx.x & 127;
    const int q = lane & 3;
    uint32_t A[128];
    float acc0[32], acc1[32];
    const uint32_t my_rows = p * 8192 + wq * 2048;
    const uint32_t peer_sb = mapa(sb, tb ^ 1);
    const uint32_t ring_desc = b_desc_lo(sb + OFF_RING);

    float sh0 = 0.f, sh1 = 0.f, sum0 = 0.f, sum1 = 0.f, sq0 = 0.f, sq1 = 0.f;
    auto load_x_block = [&](auto KB) {
      constexpr int kb = decltype(KB)::value;
      mbar_wait(sb + OFF_BAR + (B_X + 2 * kb + p) * 8, 0);
#pragma unroll
      for (int ks = 0; ks < 4; ks++)
        ldsm4(frag_addr(sb + OFF_U + kb * 16384 + my_rows, lane, ks), A[16 * kb + 4 * ks], A[16 * kb + 4 * ks + 1], A[16 * kb + 4 * ks + 2], A[16 * kb + 4 * ks + 3]);
      if (kb == 0) {
        sh0 = __shfl_sync(0xffffffffu, bf_lo(A[0]), lane & ~3);
        sh1 = __shfl_sync(0xffffffffu, bf_lo(A[1]), lane & ~3);
      }
#pragma unroll
      for (int i = 0; i < 16; i += 2) {
        const uint32_t u = A[16 * kb + i], w = A[16 * kb + i + 1];
        const float a = bf_lo(u) - sh0, b = bf_hi(u) - sh0, c = bf_lo(w) - sh1, d = bf_hi(w) - sh1;
        sum0 += a + b; sq0 = fmaf(a, a, fmaf(b, b, sq0));
        sum1 += c + d; sq1 = fmaf(c, c, fmaf(d, d, sq1));
      }
      asm volatile("" : "+f"(sum0), "+f"(sum1), "+f"(sq0), "+f"(sq1));
    };
#define IC(v) std::integral_constant<int, (v)>{}

    if (warp == 0) TSTAMP(16);
    load_x_block(IC(0));
    if (warp == 0) TSTAMP(17);
    auto j0_step = [&](auto KB) {
      constexpr int kb = decltype(KB)::value;
      issue_tile<2 * kb, 16 * kb, 4, kb == 0, false>(acc0, A, sb, ring_desc);
      issue_tile<2 * kb + 1, 16 * kb, 4, kb == 0, false>(acc1, A, sb, ring_desc);
      if constexpr (kb < 7) load_x_block(IC(kb + 1));
      if constexpr (kb < 7) { wg_wait<2>(); release_range<2 * kb - 2, 2 * kb>(sb, lane); }
    };
    j0_step(IC(0)); j0_step(IC(1)); j0_step(IC(2)); j0_step(IC(3));
    j0_step(IC(4)); j0_step(IC(5)); j0_step(IC(6));
    asm volatile("barrier.cluster.wait.aligned;" ::: "memory");
    if (lane == 0) mbar_arrive_remote(peer_sb + OFF_BAR + B_PEERX * 8);
    RowStats st;
    {
      sum0 += __shfl_xor_sync(0xffffffffu, sum0, 1); sum1 += __shfl_xor_sync(0xffffffffu, sum1, 1);
      sq0 += __shfl_xor_sync(0xffffffffu, sq0, 1); sq1 += __shfl_xor_sync(0xffffffffu, sq1, 1);
      sum0 += __shfl_xor_sync(0xffffffffu, sum0, 2); sum1 += __shfl_xor_sync(0xffffffffu, sum1, 2);
      sq0 += __shfl_xor_sync(0xffffffffu, sq0, 2); sq1 += __shfl_xor_sync(0xffffffffu, sq1, 2);
      const float m0 = sum0 * (1.f / 512.f), m1 = sum1 * (1.f / 512.f);
      const float v0 = fmaxf(sq0 * (1.f / 512.f) - m0 * m0, 0.f), v1 = fmaxf(sq1 * (1.f / 512.f) - m1 * m1, 0.f);
      st.mean0 = sh0 + m0; st.mean1 = sh1 + m1;
      st.r0 = 1.f / sqrtf(v0 + 1e-5f); st.r1 = 1.f / sqrtf(v1 + 1e-5f);
    }
    j0_step(IC(7));
    if (warp == 0) TSTAMP(18);
    const uint32_t cs_lane = sb + OFF_CS + (2 * q) * 4;
    auto epi_to_unit = [&](const float (&acc)[32], int g, int unit, int cs_col, float r0, float r1) {
      uint32_t p0, p1, p2, p3;
      epi16<false>(acc, g, cs_lane + cs_col * 4, st, r0, r1, p0, p1, p2, p3);
      stsm4(frag_addr(sb + OFF_U + unit * 16384 + my_rows, lane, g), p0, p1, p2, p3);
    };
    wg_wait<1>();
    release_range<12, 15>(sb, lane);
    fence_acc(acc0);
    mbar_wait(sb + OFF_BAR + B_CS * 8, 0);
#pragma unroll
    for (int g = 0; g < 4; g++) epi_to_unit(acc0, g, 0, 0, st.r0 * 0.25f, st.r1 * 0.25f);
    if (warp == 0) TSTAMP(19);

    issue_tile<16, 0, 4, true, false>(acc0, A, sb, ring_desc);
    wg_wait<1>(); release_range<15, 16>(sb, lane);
    fence_acc(acc1);
    epi_to_unit(acc1, 0, 1, 64, st.r0, st.r1); epi_to_unit(acc1, 1, 1, 64, st.r0, st.r1);
    issue_tile<17, 16, 4, false, false>(acc0, A, sb, ring_desc);
    epi_to_unit(acc1, 2, 1, 64, st.r0, st.r1); epi_to_unit(acc1, 3, 1, 64, st.r0, st.r1);
    issue_tile<18, 32, 4, false, false>(acc0, A, sb, ring_desc); wg_wait<2>(); release_range<16, 17>(sb, lane);
    issue_tile<19, 48, 4, false, false>(acc0, A, sb, ring_desc); retire<19, LAG>(sb, lane);
    issue_tile<20, 64, 4, false, false>(acc0, A, sb, ring_desc); retire<20, LAG>(sb, lane);
    issue_tile<21, 80, 4, false, false>(acc0, A, sb, ring_desc); retire<21, LAG>(sb, lane);
    issue_tile<22, 96, 4, false, false>(acc0, A, sb, ring_desc); retire<22, LAG>(sb, lane);
    issue_tile<23, 112, 4, false, false>(acc0, A, sb, ring_desc); retire<23, LAG>(sb, lane);

    issue_tile<24, 0, 4, true, false>(acc1, A, sb, ring_desc); retire<24, LAG>(sb, lane);
    issue_tile<25, 16, 4, false, false>(acc1, A, sb, ring_desc); retire<25, LAG>(sb, lane);
    fence_acc(acc0);
    epi_to_unit(acc0, 0, 2, 128, st.r0, st.r1); epi_to_unit(acc0, 1, 2, 128, st.r0, st.r1);
    issue_tile<26, 32, 4, false, false>(acc1, A, sb, ring_desc); retire<26, LAG>(sb, lane);
    epi_to_unit(acc0, 2, 2, 128, st.r0, st.r1); epi_to_unit(acc0, 3, 2, 128, st.r0, st.r1);
    __syncwarp();
    if (lane == 0) mbar_arrive(sb + OFF_BAR + B_QKV * 8);
    if (warp == 0) TSTAMP(20);
    issue_tile<27, 48, 4, false, false>(acc1, A, sb, ring_desc); retire<27, LAG>(sb, lane);
    issue_tile<28, 64, 4, false, false>(acc1, A, sb, ring_desc); retire<28, LAG>(sb, lane);
    issue_tile<29, 80, 4, false, false>(acc1, A, sb, ring_desc); retire<29, LAG>(sb, lane);
    issue_tile<30, 96, 4, false, false>(acc1, A, sb, ring_desc); retire<30, LAG>(sb, lane);
    issue_tile<31, 112, 4, false, false>(acc1, A, sb, ring_desc); retire<31, LAG>(sb, lane);

    const uint32_t thr16 = p * 8192 + tw * 16;
    issue_tile<32, 0, 4, true, false>(acc0, A, sb, ring_desc); retire<32, LAG>(sb, lane);
    issue_tile<33, 16, 4, false, false>(acc0, A, sb, ring_desc); retire<33, LAG>(sb, lane);
    fence_acc(acc1);
    mbar_wait_cluster(sb + OFF_BAR + B_PEERX * 8, 0);
    auto epi_f0 = [&](int g) {
      uint32_t p0, p1, p2, p3;
      epi16<true>(acc1, g, cs_lane + 192 * 4, st, st.r0, st.r1, p0, p1, p2, p3);
      sts128(sb + OFF_U + 3 * 16384 + thr16 + g * 2048, p0, p1, p2, p3);
      st_async4(peer_sb + OFF_U + 5 * 16384 + thr16 + g * 2048, peer_sb + OFF_BAR + (B_LAND + 2 + p) * 8, p0, p1, p2, p3);
    };
    epi_f0(0); epi_f0(1);
    issue_tile<34, 32, 4, false, false>(acc0, A, sb, ring_desc); retire<34, LAG>(sb, lane);
    epi_f0(2); epi_f0(3);
    issue_tile<35, 48, 4, false, false>(acc0, A, sb, ring_desc); retire<35, LAG>(sb, lane);
    issue_tile<36, 64, 4, false, false>(acc0, A, sb, ring_desc); retire<36, LAG>(sb, lane);
    issue_tile<37, 80, 4, false, false>(acc0, A, sb, ring_desc); retire<37, LAG>(sb, lane);
    issue_tile<38, 96, 4, false, false>(acc0, A, sb, ring_desc); retire<38, LAG>(sb, lane);
    issue_tile<39, 112, 4, false, false>(acc0, A, sb, ring_desc); retire<39, LAG>(sb, lane);
    if (warp == 0) TSTAMP(21);

    issue_tile<40, 0, 4, true, true>(acc1, A, sb, ring_desc); retire<40, LAG>(sb, lane);
    issue_tile<41, 16, 4, false, true>(acc1, A, sb, ring_desc); retire<41, LAG>(sb, lane);
    issue_tile<42, 32, 4, false, true>(acc1, A, sb, ring_desc); retire<42, LAG>(sb, lane);
    mbar_wait(sb + OFF_BAR + B_O * 8, 0);
#pragma unroll
    for (int g = 0; g < 4; g++) {
      ldsm4(frag_addr(sb + OFF_U + my_rows, lane, g), A[4 * g], A[4 * g + 1], A[4 * g + 2], A[4 * g + 3]);
      st_async4(peer_sb + OFF_U + 4 * 16384 + thr16 + g * 2048, peer_sb + OFF_BAR + (B_LAND + 0 + p) * 8, A[4 * g], A[4 * g + 1], A[4 * g + 2], A[4 * g + 3]);
    }
    issue_tile<43, 48, 4, false, true>(acc1, A, sb, ring_desc); retire<43, LAG>(sb, lane);
#pragma unroll
    for (int g = 0; g < 4; g++) lds128(sb + OFF_U + 3 * 16384 + thr16 + g * 2048, A[16 + 4 * g], A[17 + 4 * g], A[18 + 4 * g], A[19 + 4 * g]);
    issue_tile<44, 64, 4, false, true>(acc1, A, sb, ring_desc); retire<44, LAG>(sb, lane);
    fence_acc(acc0);
#pragma unroll
    for (int g = 0; g < 4; g++) {
      epi16<true>(acc0, g, cs_lane + 256 * 4, st, st.r0, st.r1, A[32 + 4 * g], A[33 + 4 * g], A[34 + 4 * g], A[35 + 4 * g]);
      st_async4(peer_sb + OFF_U + 6 * 16384 + thr16 + g * 2048, peer_sb + OFF_BAR + (B_LAND + 4 + p) * 8, A[32 + 4 * g], A[33 + 4 * g], A[34 + 4 * g], A[35 + 4 * g]);
    }
    issue_tile<45, 80, 4, false, true>(acc1, A, sb, ring_desc); retire<45, LAG>(sb, lane);
    mbar_wait_cluster(sb + OFF_BAR + (B_LAND + 0 + p) * 8, 0);
#pragma unroll
    for (int g = 0; g < 4; g++) lds128(sb + OFF_U + 4 * 16384 + thr16 + g * 2048, A[48 + 4 * g], A[49 + 4 * g], A[50 + 4 * g], A[51 + 4 * g]);
    issue_tile<46, 96, 4, false, true>(acc1, A, sb, ring_desc); retire<46, LAG>(sb, lane);
    mbar_wait_cluster(sb + OFF_BAR + (B_LAND + 2 + p) * 8, 0);
#pragma unroll
    for (int g = 0; g < 4; g++) lds128(sb + OFF_U + 5 * 16384 + thr16 + g * 2048, A[64 + 4 * g], A[65 + 4 * g], A[66 + 4 * g], A[67 + 4 * g]);
    issue_tile<47, 112, 4, false, true>(acc1, A, sb, ring_desc); retire<47, LAG>(sb, lane);
    if (warp == 0) TSTAMP(22);

    issue_tile<48, 0, 4, true, false>(acc0, A, sb, ring_desc); retire<48, LAG>(sb, lane);
    issue_tile<49, 16, 4, false, false>(acc0, A, sb, ring_desc); retire<49, LAG>(sb, lane);
    fence_acc(acc1);
#pragma unroll
    for (int g = 0; g < 3; g++) {
      epi16<true>(acc1, g, cs_lane + 320 * 4, st, st.r0, st.r1, A[96 + 4 * g], A[97 + 4 * g], A[98 + 4 * g], A[99 + 4 * g]);
      st_async4(peer_sb + OFF_U + 7 * 16384 + thr16 + g * 2048, peer_sb + OFF_BAR + (B_LAND + 6 + p) * 8, A[96 + 4 * g], A[97 + 4 * g], A[98 + 4 * g], A[99 + 4 * g]);
    }
    issue_tile<50, 32, 4, false, false>(acc0, A, sb, ring_desc); retire<50, LAG>(sb, lane);
    mbar_wait_cluster(sb + OFF_BAR + (B_LAND + 4 + p) * 8, 0);
#pragma unroll
    for (int g = 0; g < 4; g++) lds128(sb + OFF_U + 6 * 16384 + thr16 + g * 2048, A[80 + 4 * g], A[81 + 4 * g], A[82 + 4 * g], A[83 + 4 * g]);
    issue_tile<51, 48, 4, false, false>(acc0, A, sb, ring_desc); retire<51, LAG>(sb, lane);
    issue_tile<52, 64, 4, false, false>(acc0, A, sb, ring_desc); retire<52, LAG>(sb, lane);
    issue_tile<53, 80, 4, false, false>(acc0, A, sb, ring_desc); retire<53, LAG>(sb, lane);
    mbar_wait_cluster(sb + OFF_BAR + (B_LAND + 6 + p) * 8, 0);
#pragma unroll
    for (int g = 0; g < 3; g++) lds128(sb + OFF_U + 7 * 16384 + thr16 + g * 2048, A[112 + 4 * g], A[113 + 4 * g], A[114 + 4 * g], A[115 + 4 * g]);
    issue_tile<54, 96, 3, false, false>(acc0, A, sb, ring_desc); retire<54, LAG>(sb, lane);
    issue_tile<55, 112, 3, false, false>(acc0, A, sb, ring_desc); retire<55, LAG>(sb, lane);
    if (warp == 0) TSTAMP(23);

    auto store_partial = [&](float (&acc)[32], int blk) {
      fence_acc(acc);
      const int c = (ta + 1 + blk) & 3;
      uint4* dst = &g_part[(((((ti * 2 + tb) * 4 + c) * 4 + ta) * 2 + p) * 512) + tw];
#pragma unroll
      for (int v = 0; v < 4; v++)
        dst[v * 128] = make_uint4(pack_bf16(acc[8 * v], acc[8 * v + 1]), pack_bf16(acc[8 * v + 2], acc[8 * v + 3]),
                                  pack_bf16(acc[8 * v + 4], acc[8 * v + 5]), pack_bf16(acc[8 * v + 6], acc[8 * v + 7]));
      __syncwarp();
      if (lane == 0) mbar_arrive(sb + OFF_BAR + (B_PW + 2 * blk + p) * 8);
    };
#define P2_BLOCK(N0, ACC, PREV, PBLK)                                                         \
    issue_tile<N0 + 0, 0, 4, true, false>(ACC, A, sb, ring_desc); retire<N0 + 0, LAG>(sb, lane);           \
    issue_tile<N0 + 1, 16, 4, false, false>(ACC, A, sb, ring_desc); retire<N0 + 1, LAG>(sb, lane);         \
    store_partial(PREV, PBLK);                                                                  \
    issue_tile<N0 + 2, 32, 4, false, false>(ACC, A, sb, ring_desc); retire<N0 + 2, LAG>(sb, lane);         \
    issue_tile<N0 + 3, 48, 4, false, false>(ACC, A, sb, ring_desc); retire<N0 + 3, LAG>(sb, lane);         \
    issue_tile<N0 + 4, 64, 4, false, false>(ACC, A, sb, ring_desc); retire<N0 + 4, LAG>(sb, lane);         \
    issue_tile<N0 + 5, 80, 4, false, false>(ACC, A, sb, ring_desc); retire<N0 + 5, LAG>(sb, lane);         \
    issue_tile<N0 + 6, 96, 3, false, false>(ACC, A, sb, ring_desc); retire<N0 + 6, LAG>(sb, lane);         \
    issue_tile<N0 + 7, 112, 3, false, false>(ACC, A, sb, ring_desc); retire<N0 + 7, LAG>(sb, lane);
    P2_BLOCK(56, acc1, acc0, 0)
    P2_BLOCK(64, acc0, acc1, 1)
    P2_BLOCK(72, acc1, acc0, 2)
    if (warp == 0) TSTAMP(24);

    uint32_t res[16];
    mbar_wait(sb + OFF_BAR + (B_RES + p) * 8, 0);
#pragma unroll
    for (int g = 0; g < 4; g++) ldsm4(frag_addr(sb + OFF_U + 16384 + my_rows, lane, g), res[4 * g], res[4 * g + 1], res[4 * g + 2], res[4 * g + 3]);
    mbar_wait(sb + OFF_BAR + (B_PR + p) * 8, 0);
    if (warp == 0) TSTAMP(25);
    {
      const uint4* src = &g_part[((((ti * 2 + tb) * 4 + ta) * 4) * 2 + p) * 512 + tw];
      uint4 pv[3][4];
#pragma unroll
      for (int s = 0; s < 3; s++) {
        const int sa = (ta + 1 + s) & 3;
#pragma unroll
        for (int v = 0; v < 4; v++) pv[s][v] = ldg_cg(src + sa * 1024 + v * 128);
      }
      wg_wait<0>();
      fence_acc(acc1);
#pragma unroll
      for (int v = 0; v < 4; v++) {
        float y[8];
#pragma unroll
        for (int e = 0; e < 4; e++) {
          const uint32_t r = res[4 * v + e];
          const uint32_t a = e == 0 ? pv[0][v].x : e == 1 ? pv[0][v].y : e == 2 ? pv[0][v].z : pv[0][v].w;
          const uint32_t b = e == 0 ? pv[1][v].x : e == 1 ? pv[1][v].y : e == 2 ? pv[1][v].z : pv[1][v].w;
          const uint32_t c = e == 0 ? pv[2][v].x : e == 1 ? pv[2][v].y : e == 2 ? pv[2][v].z : pv[2][v].w;
          y[2 * e] = ((acc1[8 * v + 2 * e] + bf_lo(a)) + (bf_lo(b) + bf_lo(c))) + bf_lo(r);
          y[2 * e + 1] = ((acc1[8 * v + 2 * e + 1] + bf_hi(a)) + (bf_hi(b) + bf_hi(c))) + bf_hi(r);
        }
        stsm4(frag_addr(sb + OFF_U + 2 * 16384 + my_rows, lane, v), pack_bf16(y[0], y[1]), pack_bf16(y[2], y[3]), pack_bf16(y[4], y[5]), pack_bf16(y[6], y[7]));
      }
    }
    asm volatile("fence.proxy.async.shared::cta;" ::: "memory");
    bar_sync(1 + p, 128);
    if (wq == 0) {
      if (elect_one()) {
        tma_store(&tmOut, sb + OFF_U + 2 * 16384 + p * 8192, 512 * p + 256 * tb + 64 * ta, 64 * ti);
        asm volatile("cp.async.bulk.commit_group;" ::: "memory");
        asm volatile("cp.async.bulk.wait_group.read 0;" ::: "memory");
      }
      __syncwarp();
    }
    if (warp == 0) TSTAMP(26);
  }
}

typedef CUresult (*EncodeFn)(CUtensorMap*, CUtensorMapDataType, cuuint32_t, void*, const cuuint64_t*, const cuuint64_t*,
                             const cuuint32_t*, const cuuint32_t*, CUtensorMapInterleave, CUtensorMapSwizzle,
                             CUtensorMapL2promotion, CUtensorMapFloatOOBfill);

CUtensorMap make_map(EncodeFn fn, const void* ptr, uint64_t rows, uint64_t cols) {
  CUtensorMap m;
  cuuint64_t dims[2] = {cols, rows};
  cuuint64_t strides[1] = {cols * 2};
  cuuint32_t box[2] = {64, 64};
  cuuint32_t es[2] = {1, 1};
  fn(&m, CU_TENSOR_MAP_DATA_TYPE_BFLOAT16, 2, const_cast<void*>(ptr), dims, strides, box, es, CU_TENSOR_MAP_INTERLEAVE_NONE,
     CU_TENSOR_MAP_SWIZZLE_128B, CU_TENSOR_MAP_L2_PROMOTION_L2_128B, CU_TENSOR_MAP_FLOAT_OOB_FILL_NONE);
  return m;
}

}

extern "C" void kernel_launch(void* const* d_in, const int* in_sizes, int n_in, void* d_out, int out_size) {
  (void)in_sizes; (void)n_in; (void)out_size;
  const __nv_bfloat16* x = (const __nv_bfloat16*)d_in[0];
  const __nv_bfloat16* wqkv = (const __nv_bfloat16*)d_in[1];
  const __nv_bfloat16* wo = (const __nv_bfloat16*)d_in[2];
  const __nv_bfloat16* w1 = (const __nv_bfloat16*)d_in[4];
  const __nv_bfloat16* w2 = (const __nv_bfloat16*)d_in[5];

  static EncodeFn encode = nullptr;
  if (!encode) {
    void* fn = nullptr;
    cudaDriverEntryPointQueryResult qr;
    cudaGetDriverEntryPoint("cuTensorMapEncodeTiled", &fn, cudaEnableDefault, &qr);
    encode = (EncodeFn)fn;
    cudaFuncSetAttribute(fused_kernel, cudaFuncAttributeMaxDynamicSharedMemorySize, SMEM_BYTES);
  }
  const CUtensorMap tmX = make_map(encode, x, 1024, 1024);
  const CUtensorMap tmWqkv = make_map(encode, wqkv, 512, 1536);
  const CUtensorMap tmW1 = make_map(encode, w1, 512, kF);
  const CUtensorMap tmWo = make_map(encode, wo, 512, 512);
  const CUtensorMap tmW2 = make_map(encode, w2, kF, 512);
  const CUtensorMap tmOut = make_map(encode, d_out, 1024, 1024);
  Params prm{wqkv, w1};

  cudaLaunchConfig_t cfg = {};
  cfg.gridDim = dim3(128);
  cfg.blockDim = dim3(384);
  cfg.dynamicSmemBytes = SMEM_BYTES;
  cfg.stream = cudaStreamPerThread;
  cudaLaunchAttribute at[1];
  at[0].id = cudaLaunchAttributeClusterDimension;
  at[0].val.clusterDim.x = 2; at[0].val.clusterDim.y = 1; at[0].val.clusterDim.z = 1;
  cfg.attrs = at; cfg.numAttrs = 1;
  cudaLaunchKernelEx(&cfg, fused_kernel, tmX, tmWqkv, tmW1, tmWo, tmW2, tmOut, prm);
}
```

```cpp
#include <cuda_runtime.h>
#include <cuda_bf16.h>
#include <cuda.h>
#include <stdint.h>
#include <type_traits>

namespace {

constexpr int kS = 2048, kD = 512, kF = 1376;
constexpr int kFS = 176;
constexpr int kCS = 192 + kFS;
constexpr int RING = 5;
constexpr int NTILE = 80;
constexpr int NDS = NTILE / 2;
constexpr int LAG = 2;

constexpr uint32_t OFF_U = 0;
constexpr uint32_t OFF_RING = 8 * 16384;
constexpr uint32_t OFF_HALO = OFF_RING + RING * 16384;
constexpr uint32_t OFF_CS = OFF_HALO + 4096;
constexpr uint32_t OFF_ST = OFF_CS + 1536;
constexpr uint32_t OFF_BAR = OFF_ST + 1024;
constexpr int B_FULL = 0, B_EMPTY = B_FULL + RING, B_X = B_EMPTY + RING  , B_LAND = B_X + 16  ,
              B_RES = B_LAND + 8  , B_QKV = B_RES + 2, B_O = B_QKV + 1, B_CS = B_O + 1, B_PEERX = B_CS + 1,
              B_PW = B_PEERX + 1  , B_PR = B_PW + 6  , B_HALO = B_PR + 2, B_COUNT = B_HALO + 1;
constexpr uint32_t SMEM_USED = OFF_BAR + B_COUNT * 8;
constexpr uint32_t SMEM_BYTES = SMEM_USED + 1024;

constexpr int SPIN_LIMIT = 1 << 22;

__device__ uint4 g_cs[8 * 96];
__device__ uint4 g_st[16 * 64];
__device__ uint4 g_halo[16 * 8 * 256];
__device__ uint32_t g_halo_flag[16 * 8 * 8];
__device__ uint4 g_part[16 * 2 * 4 * 4 * 2 * 512];
__device__ uint32_t g_part_flag[16 * 2 * 4 * 8];
__device__ uint32_t g_launch_cnt[128];

__device__ __forceinline__ uint32_t smem_u32(const void* p) { return (uint32_t)__cvta_generic_to_shared(p); }
__device__ __forceinline__ void mbar_init(uint32_t bar, uint32_t count) {
  asm volatile("mbarrier.init.shared::cta.b64 [%0], %1;" ::"r"(bar), "r"(count));
}
__device__ __forceinline__ void mbar_expect_tx(uint32_t bar, uint32_t bytes) {
  asm volatile("mbarrier.arrive.expect_tx.shared::cta.b64 _, [%0], %1;" ::"r"(bar), "r"(bytes) : "memory");
}
__device__ __forceinline__ void mbar_arrive(uint32_t bar) {
  asm volatile("mbarrier.arrive.shared::cta.b64 _, [%0];" ::"r"(bar) : "memory");
}
__device__ __forceinline__ void mbar_arrive_remote(uint32_t bar_cluster) {
  asm volatile("mbarrier.arrive.shared::cluster.b64 _, [%0];" ::"r"(bar_cluster) : "memory");
}
__device__ __forceinline__ void mbar_wait(uint32_t bar, uint32_t parity) {
  asm volatile("{\n.reg .pred p, q;\n.reg .u32 c;\nmov.u32 c, 0;\n"
               "WAIT_LOOP:\nmbarrier.try_wait.parity.shared::cta.b64 p, [%0], %1;\n@p bra WAIT_DONE;\n"
               "add.u32 c, c, 1;\nsetp.gt.u32 q, c, %2;\n@q trap;\nbra WAIT_LOOP;\nWAIT_DONE:\n}\n"
               ::"r"(bar), "r"(parity), "n"(SPIN_LIMIT) : "memory");
}
__device__ __forceinline__ void mbar_wait_cluster(uint32_t bar, uint32_t parity) {
  asm volatile("{\n.reg .pred p, q;\n.reg .u32 c;\nmov.u32 c, 0;\n"
               "WAIT_LOOP:\nmbarrier.try_wait.parity.acquire.cluster.shared::cta.b64 p, [%0], %1;\n@p bra WAIT_DONE;\n"
               "add.u32 c, c, 1;\nsetp.gt.u32 q, c, %2;\n@q trap;\nbra WAIT_LOOP;\nWAIT_DONE:\n}\n"
               ::"r"(bar), "r"(parity), "n"(SPIN_LIMIT) : "memory");
}
__device__ __forceinline__ bool elect_one() {
  uint32_t pred;
  asm volatile("{\n.reg .pred p;\nelect.sync _|p, 0xffffffff;\nselp.u32 %0, 1, 0, p;\n}\n" : "=r"(pred));
  return pred;
}
__device__ __forceinline__ void tma_load(uint32_t dst, const CUtensorMap* tm, uint32_t bar, int c0, int c1) {
  asm volatile("cp.async.bulk.tensor.2d.shared::cluster.global.mbarrier::complete_tx::bytes [%0], [%1, {%3, %4}], [%2];"
               ::"r"(dst), "l"(tm), "r"(bar), "r"(c0), "r"(c1) : "memory");
}
__device__ __forceinline__ void tma_prefetch(const CUtensorMap* tm, int c0, int c1) {
  asm volatile("cp.async.bulk.prefetch.tensor.2d.L2.global [%0, {%1, %2}];" ::"l"(tm), "r"(c0), "r"(c1) : "memory");
}
__device__ __forceinline__ void prefetch_tmap(const CUtensorMap* tm) {
  asm volatile("prefetch.tensormap [%0];" ::"l"(tm) : "memory");
}
__device__ __forceinline__ uint32_t mapa(uint32_t addr, uint32_t rank) {
  uint32_t r;
  asm("mapa.shared::cluster.u32 %0, %1, %2;" : "=r"(r) : "r"(addr), "r"(rank));
  return r;
}
__device__ __forceinline__ void st_async4(uint32_t addr, uint32_t bar, uint32_t a, uint32_t b, uint32_t c, uint32_t d) {
  asm volatile("st.async.weak.shared::cluster.mbarrier::complete_tx::bytes.v4.b32 [%0], {%2, %3, %4, %5}, [%1];"
               ::"r"(addr), "r"(bar), "r"(a), "r"(b), "r"(c), "r"(d) : "memory");
}
__device__ __forceinline__ void ldsm4(uint32_t addr, uint32_t& a, uint32_t& b, uint32_t& c, uint32_t& d) {
  asm volatile("ldmatrix.sync.aligned.m8n8.x4.shared.b16 {%0, %1, %2, %3}, [%4];"
               : "=r"(a), "=r"(b), "=r"(c), "=r"(d) : "r"(addr) : "memory");
}
__device__ __forceinline__ void ldsm2(uint32_t addr, uint32_t& a, uint32_t& b) {
  asm volatile("ldmatrix.sync.aligned.m8n8.x2.shared.b16 {%0, %1}, [%2];" : "=r"(a), "=r"(b) : "r"(addr) : "memory");
}
__device__ __forceinline__ void ldsm4t(uint32_t addr, uint32_t& a, uint32_t& b, uint32_t& c, uint32_t& d) {
  asm volatile("ldmatrix.sync.aligned.m8n8.x4.trans.shared.b16 {%0, %1, %2, %3}, [%4];"
               : "=r"(a), "=r"(b), "=r"(c), "=r"(d) : "r"(addr) : "memory");
}
__device__ __forceinline__ void ldsm2t(uint32_t addr, uint32_t& a, uint32_t& b) {
  asm volatile("ldmatrix.sync.aligned.m8n8.x2.trans.shared.b16 {%0, %1}, [%2];" : "=r"(a), "=r"(b) : "r"(addr) : "memory");
}
__device__ __forceinline__ void stsm4(uint32_t addr, uint32_t a, uint32_t b, uint32_t c, uint32_t d) {
  asm volatile("stmatrix.sync.aligned.m8n8.x4.shared.b16 [%0], {%1, %2, %3, %4};"
               ::"r"(addr), "r"(a), "r"(b), "r"(c), "r"(d) : "memory");
}
__device__ __forceinline__ void lds128(uint32_t addr, uint32_t& a, uint32_t& b, uint32_t& c, uint32_t& d) {
  asm volatile("ld.shared.v4.b32 {%0, %1, %2, %3}, [%4];" : "=r"(a), "=r"(b), "=r"(c), "=r"(d) : "r"(addr) : "memory");
}
__device__ __forceinline__ void sts128(uint32_t addr, uint32_t a, uint32_t b, uint32_t c, uint32_t d) {
  asm volatile("st.shared.v4.b32 [%0], {%1, %2, %3, %4};" ::"r"(addr), "r"(a), "r"(b), "r"(c), "r"(d) : "memory");
}
__device__ __forceinline__ float2 lds64f(uint32_t addr) {
  float2 v;
  asm volatile("ld.shared.v2.f32 {%0, %1}, [%2];" : "=f"(v.x), "=f"(v.y) : "r"(addr) : "memory");
  return v;
}
__device__ __forceinline__ uint32_t pack_bf16(float lo, float hi) {
  uint32_t r;
  asm("cvt.rn.bf16x2.f32 %0, %1, %2;" : "=r"(r) : "f"(hi), "f"(lo));
  return r;
}
__device__ __forceinline__ uint32_t pack_bf16_relu(float lo, float hi) {
  uint32_t r;
  asm("cvt.rn.relu.bf16x2.f32 %0, %1, %2;" : "=r"(r) : "f"(hi), "f"(lo));
  return r;
}
__device__ __forceinline__ float ex2(float x) { float y; asm("ex2.approx.ftz.f32 %0, %1;" : "=f"(y) : "f"(x)); return y; }
__device__ __forceinline__ float bf_lo(uint32_t v) { return __uint_as_float(v << 16); }
__device__ __forceinline__ float bf_hi(uint32_t v) { return __uint_as_float(v & 0xffff0000u); }
__device__ __forceinline__ void publish_flag(uint32_t* p, uint32_t v) {
  asm volatile("fence.acq_rel.gpu;\nst.relaxed.gpu.global.u32 [%0], %1;" ::"l"(p), "r"(v) : "memory");
}
__device__ __forceinline__ void poll_flag(const uint32_t* ptr, uint32_t e) {
  asm volatile("{\n.reg .pred p, q;\n.reg .u32 c, v;\nmov.u32 c, 0;\n"
               "POLL_LOOP:\nld.acquire.gpu.global.u32 v, [%0];\nsetp.eq.u32 p, v, %1;\n@p bra POLL_DONE;\n"
               "add.u32 c, c, 1;\nsetp.gt.u32 q, c, %2;\n@q trap;\nbra POLL_LOOP;\nPOLL_DONE:\n}\n"
               ::"l"(ptr), "r"(e), "n"(SPIN_LIMIT) : "memory");
}
__device__ __forceinline__ uint4 ldg_cg(const uint4* p) {
  uint4 v;
  asm volatile("ld.global.cg.v4.u32 {%0, %1, %2, %3}, [%4];" : "=r"(v.x), "=r"(v.y), "=r"(v.z), "=r"(v.w) : "l"(p) : "memory");
  return v;
}
__device__ __forceinline__ void bar_sync(int id, int n) { asm volatile("bar.sync %0, %1;" ::"r"(id), "r"(n) : "memory"); }
__device__ __forceinline__ void wg_fence() { asm volatile("wgmma.fence.sync.aligned;" ::: "memory"); }
__device__ __forceinline__ void wg_commit() { asm volatile("wgmma.commit_group.sync.aligned;" ::: "memory"); }
template <int N> __device__ __forceinline__ void wg_wait() { asm volatile("wgmma.wait_group.sync.aligned %0;" ::"n"(N) : "memory"); }
__device__ __forceinline__ void fence_acc(float (&d)[32]) {
#pragma unroll
  for (int i = 0; i < 32; i++) asm volatile("" : "+f"(d[i])::"memory");
}
__device__ __forceinline__ uint64_t b_desc(uint32_t saddr) {
  return (uint64_t)((saddr & 0x3FFFF) >> 4) | ((uint64_t)(8192 >> 4) << 16) | ((uint64_t)(1024 >> 4) << 32) | ((uint64_t)1 << 62);
}
__device__ __forceinline__ void mma16816(float (&c)[4], uint32_t a0, uint32_t a1, uint32_t a2, uint32_t a3, uint32_t b0, uint32_t b1) {
  asm volatile("mma.sync.aligned.m16n8k16.row.col.f32.bf16.bf16.f32 {%0, %1, %2, %3}, {%4, %5, %6, %7}, {%8, %9}, {%0, %1, %2, %3};"
               : "+f"(c[0]), "+f"(c[1]), "+f"(c[2]), "+f"(c[3]) : "r"(a0), "r"(a1), "r"(a2), "r"(a3), "r"(b0), "r"(b1));
}
__device__ __forceinline__ void mma1688(float (&c)[4], uint32_t a0, uint32_t a1, uint32_t b0) {
  asm volatile("mma.sync.aligned.m16n8k8.row.col.f32.bf16.bf16.f32 {%0, %1, %2, %3}, {%4, %5}, {%6}, {%0, %1, %2, %3};"
               : "+f"(c[0]), "+f"(c[1]), "+f"(c[2]), "+f"(c[3]) : "r"(a0), "r"(a1), "r"(b0));
}

template <int OFF, int SCALE_D>
__device__ __forceinline__ void wgmma_rs_n64(float (&d)[32], uint32_t a0, uint32_t a1, uint32_t a2, uint32_t a3, uint64_t desc) {
  asm volatile("{\n.reg .pred p;\n.reg .b64 db;\nadd.s64 db, %36, %37;\n"
    "setp.ne.b32 p, %38, 0;\n"
    "wgmma.mma_async.sync.aligned.m64n64k16.f32.bf16.bf16 "
    "{%0, %1, %2, %3, %4, %5, %6, %7, %8, %9, %10, %11, %12, %13, %14, %15, %16, %17, %18, %19, %20, %21, %22, %23, %24, %25, %26, %27, %28, %29, %30, %31}, "
    "{%32,%33,%34,%35}, db, p, 1, 1, 1;\n}\n"
    : "+f"(d[0]), "+f"(d[1]), "+f"(d[2]), "+f"(d[3]), "+f"(d[4]), "+f"(d[5]), "+f"(d[6]), "+f"(d[7]), "+f"(d[8]), "+f"(d[9]), "+f"(d[10]), "+f"(d[11]), "+f"(d[12]), "+f"(d[13]), "+f"(d[14]), "+f"(d[15]), "+f"(d[16]), "+f"(d[17]), "+f"(d[18]), "+f"(d[19]), "+f"(d[20]), "+f"(d[21]), "+f"(d[22]), "+f"(d[23]), "+f"(d[24]), "+f"(d[25]), "+f"(d[26]), "+f"(d[27]), "+f"(d[28]), "+f"(d[29]), "+f"(d[30]), "+f"(d[31])
    : "r"(a0), "r"(a1), "r"(a2), "r"(a3), "l"(desc), "n"(OFF), "n"(SCALE_D));
}
template <int OFF, int SCALE_D>
__device__ __forceinline__ void wgmma_rs_n48(float (&d)[32], uint32_t a0, uint32_t a1, uint32_t a2, uint32_t a3, uint64_t desc) {
  asm volatile("{\n.reg .pred p;\n.reg .b64 db;\nadd.s64 db, %28, %29;\n"
    "setp.ne.b32 p, %30, 0;\n"
    "wgmma.mma_async.sync.aligned.m64n48k16.f32.bf16.bf16 "
    "{%0, %1, %2, %3, %4, %5, %6, %7, %8, %9, %10, %11, %12, %13, %14, %15, %16, %17, %18, %19, %20, %21, %22, %23}, "
    "{%24,%25,%26,%27}, db, p, 1, 1, 1;\n}\n"
    : "+f"(d[0]), "+f"(d[1]), "+f"(d[2]), "+f"(d[3]), "+f"(d[4]), "+f"(d[5]), "+f"(d[6]), "+f"(d[7]), "+f"(d[8]), "+f"(d[9]), "+f"(d[10]), "+f"(d[11]), "+f"(d[12]), "+f"(d[13]), "+f"(d[14]), "+f"(d[15]), "+f"(d[16]), "+f"(d[17]), "+f"(d[18]), "+f"(d[19]), "+f"(d[20]), "+f"(d[21]), "+f"(d[22]), "+f"(d[23])
    : "r"(a0), "r"(a1), "r"(a2), "r"(a3), "l"(desc), "n"(OFF), "n"(SCALE_D));
}

#define TSTAMP(idx) do {} while (0)

struct Params {
  const __nv_bfloat16* x;
  const __nv_bfloat16* wqkv;
  const __nv_bfloat16* w1;
  __nv_bfloat16* out;
};

template <int n, int AOFF, int NKS, bool FIRST, bool N48>
__device__ __forceinline__ void issue_tile(float (&acc)[32], const uint32_t (&A)[128], uint32_t sb, uint64_t ring_desc) {
  constexpr int m = n / 2, s = m % RING;
  if constexpr ((n & 1) == 0) mbar_wait(sb + OFF_BAR + (B_FULL + s) * 8, (m / RING) & 1);
  wg_fence();
  auto step = [&](auto KS) {
    constexpr int ks = decltype(KS)::value;
    if constexpr (ks < NKS) {
      constexpr int off = (s * 16384 + (n & 1) * 8192 + ks * 2048) >> 4;
      constexpr int sc = (FIRST && ks == 0) ? 0 : 1;
      if constexpr (N48) wgmma_rs_n48<off, sc>(acc, A[AOFF + 4 * ks], A[AOFF + 4 * ks + 1], A[AOFF + 4 * ks + 2], A[AOFF + 4 * ks + 3], ring_desc);
      else wgmma_rs_n64<off, sc>(acc, A[AOFF + 4 * ks], A[AOFF + 4 * ks + 1], A[AOFF + 4 * ks + 2], A[AOFF + 4 * ks + 3], ring_desc);
    }
  };
  step(std::integral_constant<int, 0>{}); step(std::integral_constant<int, 1>{});
  step(std::integral_constant<int, 2>{}); step(std::integral_constant<int, 3>{});
  wg_commit();
}
template <int t>
__device__ __forceinline__ void release_tile(uint32_t sb, int lane) {
  if constexpr (t >= 0 && (t & 1) == 1 && t / 2 + RING < NDS) {
    if (lane == 0) mbar_arrive(sb + OFF_BAR + (B_EMPTY + (t / 2) % RING) * 8);
  }
}
template <int n, int L>
__device__ __forceinline__ void retire(uint32_t sb, int lane) {
  wg_wait<L>();
  release_tile<n - L>(sb, lane);
}

struct RowStats { float mean0, mean1, r0, r1; };

template <bool RELU>
__device__ __forceinline__ void epi16(const float (&acc)[32], int g, uint32_t cs_addr, const RowStats& st, float r0, float r1,
                                      uint32_t& p0, uint32_t& p1, uint32_t& p2, uint32_t& p3) {
  const float2 c0 = lds64f(cs_addr + (16 * g) * 4);
  const float2 c1 = lds64f(cs_addr + (16 * g + 8) * 4);
  const float y0 = fmaf(-st.mean0, c0.x, acc[8 * g + 0]) * r0, y1 = fmaf(-st.mean0, c0.y, acc[8 * g + 1]) * r0;
  const float y2 = fmaf(-st.mean1, c0.x, acc[8 * g + 2]) * r1, y3 = fmaf(-st.mean1, c0.y, acc[8 * g + 3]) * r1;
  const float y4 = fmaf(-st.mean0, c1.x, acc[8 * g + 4]) * r0, y5 = fmaf(-st.mean0, c1.y, acc[8 * g + 5]) * r0;
  const float y6 = fmaf(-st.mean1, c1.x, acc[8 * g + 6]) * r1, y7 = fmaf(-st.mean1, c1.y, acc[8 * g + 7]) * r1;
  if (RELU) { p0 = pack_bf16_relu(y0, y1); p1 = pack_bf16_relu(y2, y3); p2 = pack_bf16_relu(y4, y5); p3 = pack_bf16_relu(y6, y7); }
  else { p0 = pack_bf16(y0, y1); p1 = pack_bf16(y2, y3); p2 = pack_bf16(y4, y5); p3 = pack_bf16(y6, y7); }
}

__device__ __forceinline__ uint32_t frag_addr(uint32_t tile_row0_addr, int lane, int g) {
  const int r = (lane & 7) + (lane & 8);
  const int chunk = 2 * g + (lane >> 4);
  return tile_row0_addr + r * 128 + ((chunk ^ (lane & 7)) << 4);
}

#define IC(v) std::integral_constant<int, (v)>{}
template <int I, int E, class F>
__device__ __forceinline__ void static_for(F&& f) {
  if constexpr (I < E) { f(std::integral_constant<int, I>{}); static_for<I + 1, E>(f); }
}

__global__ void __cluster_dims__(2, 1, 1) __launch_bounds__(384, 1)
fused_kernel(const __grid_constant__ CUtensorMap tmX, const __grid_constant__ CUtensorMap tmWqkv,
             const __grid_constant__ CUtensorMap tmW1, const __grid_constant__ CUtensorMap tmWo,
             const __grid_constant__ CUtensorMap tmW2, Params prm) {
  extern __shared__ uint8_t smem_raw[];
  const uint32_t sb = (smem_u32(smem_raw) + 1023u) & ~1023u;
  const int warp = __shfl_sync(0xffffffffu, threadIdx.x >> 5, 0);
  const int lane = threadIdx.x & 31;
  const int ti = blockIdx.x >> 3;
  const int tj = blockIdx.x & 7;
  const int ta = tj >> 1, tb = tj & 1;

  if (warp == 8 && elect_one()) {
    prefetch_tmap(&tmX); prefetch_tmap(&tmWqkv); prefetch_tmap(&tmW1); prefetch_tmap(&tmWo); prefetch_tmap(&tmW2);
  }
  if (threadIdx.x < B_COUNT) {
    const int t = threadIdx.x;
    const uint32_t bar = sb + OFF_BAR + t * 8;
    uint32_t cnt = 1;
    if ((t >= B_EMPTY && t < B_X) || t == B_QKV || t == B_PEERX || t == B_O) cnt = 8;
    else if (t == B_CS) cnt = 3;
    else if (t >= B_PW && t < B_PR) cnt = 4;
    mbar_init(bar, cnt);
    if (t >= B_X && t < B_QKV) mbar_expect_tx(bar, (t >= B_LAND + 6 && t < B_RES) ? 6144 : 8192);
    asm volatile("fence.mbarrier_init.release.cluster;" ::: "memory");
  }
  __syncthreads();
  asm volatile("barrier.cluster.arrive.relaxed.aligned;" ::: "memory");

  if (warp >= 8) {
    asm volatile("setmaxnreg.dec.sync.aligned.u32 56;");
    if (warp == 8) {
      TSTAMP(0);
      uint32_t slot = 0, ph = 1;
      auto load_pair = [&](const CUtensorMap* m0, int c0, int r0, const CUtensorMap* m1, int c1, int r1) {
        mbar_wait(sb + OFF_BAR + (B_EMPTY + slot) * 8, ph);
        if (elect_one()) {
          const uint32_t bar = sb + OFF_BAR + (B_FULL + slot) * 8, dst = sb + OFF_RING + slot * 16384;
          mbar_expect_tx(bar, 16384);
          tma_load(dst, m0, bar, c0, r0);
          tma_load(dst + 8192, m1, bar, c1, r1);
        }
        __syncwarp();
        if (++slot == RING) { slot = 0; ph ^= 1; }
      };
#pragma unroll 1
      for (int kb = 0; kb < 8; kb++) {
        if (elect_one()) {
          tma_load(sb + OFF_U + kb * 16384, &tmX, sb + OFF_BAR + (B_X + 2 * kb) * 8, 64 * kb, 64 * ti);
          tma_load(sb + OFF_U + kb * 16384 + 8192, &tmX, sb + OFF_BAR + (B_X + 2 * kb + 1) * 8, 512 + 64 * kb, 64 * ti);
        }
        __syncwarp();
        load_pair(&tmWqkv, 64 * tj, 64 * kb, &tmWqkv, 512 + 64 * tj, 64 * kb);
        if (kb == 4) {
          TSTAMP(36);
          if (elect_one()) {
#pragma unroll 1
            for (int m = 2 * ti; m < 2 * ti + 2; m++) {
              if (m < 8) tma_prefetch(&tmWqkv, 1024 + 64 * tj, 64 * m);
              else tma_prefetch(&tmW1, kFS * tj + 64 * ((m - 8) >> 3), 64 * ((m - 8) & 7));
              const int t = m & 7, c0 = 256 * tb + 64 * (m >> 3);
              const int jj = (t == 1 || t == 4 || t == 5 || t == 7) ? (tj ^ 1) : tj;
              if (t < 2) tma_prefetch(&tmWo, c0, 64 * jj);
              else tma_prefetch(&tmW2, c0, kFS * jj + (t >= 6 ? 128 : ((t == 3 || t == 5) ? 64 : 0)));
            }
          }
          __syncwarp();
        }
      }
#pragma unroll 1
      for (int it = 0; it < 16; it++) {
        const int job = it >> 2, r = 128 * (it & 3);
        const CUtensorMap* tm = job == 0 ? &tmWqkv : &tmW1;
        const int c0 = job == 0 ? 1024 + 64 * tj : kFS * tj + 64 * (job - 1);
        load_pair(tm, c0, r, tm, c0, r + 64);
      }
#pragma unroll 1
      for (int blk = 0; blk < 4; blk++) {
        const int c0 = 256 * tb + 64 * ((ta + 1 + blk) & 3);
        const int ro = kFS * tj, rp = kFS * (tj ^ 1);
        load_pair(&tmWo, c0, 64 * tj, &tmWo, c0, 64 * (tj ^ 1));
        load_pair(&tmW2, c0, ro, &tmW2, c0, ro + 64);
        load_pair(&tmW2, c0, rp, &tmW2, c0, rp + 64);
        load_pair(&tmW2, c0, ro + 128, &tmW2, c0, rp + 128);
        if (blk == 0) {
          mbar_wait(sb + OFF_BAR + B_O * 8, 0);
          if (elect_one()) {
            asm volatile("fence.proxy.async.shared::cta;" ::: "memory");
            tma_load(sb + OFF_U + 16384, &tmX, sb + OFF_BAR + B_RES * 8, 256 * tb + 64 * ta, 64 * ti);
            tma_load(sb + OFF_U + 16384 + 8192, &tmX, sb + OFF_BAR + (B_RES + 1) * 8, 512 + 256 * tb + 64 * ta, 64 * ti);
          }
          __syncwarp();
        }
      }
      TSTAMP(1);
    } else {
      const int hw = warp - 9, ht = threadIdx.x - 288;
      const uint32_t epoch = g_launch_cnt[blockIdx.x] + 1;
      {
        const uint32_t tag = epoch & 3u;
        const int ch = 3 * ti + hw;
        if (ch < kCS / 8) {
          const __nv_bfloat16* src; int pitch; bool ok = true;
          if (ch < 24) { src = prm.wqkv + 512 * (ch >> 3) + 64 * tj + 8 * (ch & 7); pitch = 1536; }
          else { const int c = kFS * tj + 8 * (ch - 24); src = prm.w1 + c; pitch = kF; ok = c < kF; }
          float sm[8] = {0.f, 0.f, 0.f, 0.f, 0.f, 0.f, 0.f, 0.f};
          if (ok) {
            src += (size_t)lane * pitch;
#pragma unroll
            for (int half = 0; half < 2; half++) {
              uint4 v[8];
#pragma unroll
              for (int k = 0; k < 8; k++) v[k] = __ldg(reinterpret_cast<const uint4*>(src + (size_t)(32 * (8 * half + k)) * pitch));
#pragma unroll
              for (int k = 0; k < 8; k++) {
                sm[0] += bf_lo(v[k].x); sm[1] += bf_hi(v[k].x); sm[2] += bf_lo(v[k].y); sm[3] += bf_hi(v[k].y);
                sm[4] += bf_lo(v[k].z); sm[5] += bf_hi(v[k].z); sm[6] += bf_lo(v[k].w); sm[7] += bf_hi(v[k].w);
              }
            }
          }
          const bool b4 = lane & 16, b3 = lane & 8, b2 = lane & 4;
#pragma unroll
          for (int k = 0; k < 4; k++) { const float snd = b4 ? sm[k] : sm[k + 4], keep = b4 ? sm[k + 4] : sm[k]; sm[k] = keep + __shfl_xor_sync(0xffffffffu, snd, 16); }
#pragma unroll
          for (int k = 0; k < 2; k++) { const float snd = b3 ? sm[k] : sm[k + 2], keep = b3 ? sm[k + 2] : sm[k]; sm[k] = keep + __shfl_xor_sync(0xffffffffu, snd, 8); }
          { const float snd = b2 ? sm[0] : sm[1], keep = b2 ? sm[1] : sm[0]; sm[0] = keep + __shfl_xor_sync(0xffffffffu, snd, 4); }
          sm[0] += __shfl_xor_sync(0xffffffffu, sm[0], 2);
          sm[0] += __shfl_xor_sync(0xffffffffu, sm[0], 1);
          if ((lane & 3) == 0) {
            const int col = (b4 ? 4 : 0) + (b3 ? 2 : 0) + (b2 ? 1 : 0);
            const uint32_t w = (__float_as_uint(sm[0]) & ~3u) | tag;
            asm volatile("st.relaxed.gpu.global.u32 [%0], %1;" ::"l"(reinterpret_cast<uint32_t*>(g_cs) + tj * 384 + ch * 8 + col), "r"(w) : "memory");
          }
        }
        if (hw == 0) TSTAMP(13);
        auto gather = [&](const uint4* src, uint32_t dst) {
          uint4 v;
          int it = 0;
          while (true) {
            asm volatile("ld.relaxed.gpu.global.v4.u32 {%0, %1, %2, %3}, [%4];" : "=r"(v.x), "=r"(v.y), "=r"(v.z), "=r"(v.w) : "l"(src) : "memory");
            if (((v.x & 3u) == tag && (v.y & 3u) == tag && (v.z & 3u) == tag && (v.w & 3u) == tag) || ++it > SPIN_LIMIT) break;
          }
          sts128(dst, v.x, v.y, v.z, v.w);
        };
        if (ht < 64) gather(&g_st[ti * 64 + ht], sb + OFF_ST + ht * 16);
        if (ht < kCS / 4) gather(&g_cs[tj * 96 + ht], sb + OFF_CS + ht * 16);
        __syncwarp();
        if (lane == 0) mbar_arrive(sb + OFF_BAR + B_CS * 8);
        TSTAMP(2 + hw);
      }
      mbar_wait(sb + OFF_BAR + B_QKV * 8, 0);
      TSTAMP(5 + hw);
      if (ht == 0) g_launch_cnt[blockIdx.x] = epoch;
      if (hw == 2) {
        const uint32_t Kt = sb + OFF_U + 16384, Vt = sb + OFF_U + 32768;
        if (ti < 15) {
          uint4* dst = &g_halo[(ti * 8 + tj) * 256];
#pragma unroll
          for (int u = 0; u < 4; u++) {
            const uint32_t src = (u < 2 ? Kt : Vt) + (u & 1) * 8192 + 56 * 128;
#pragma unroll
            for (int v = 0; v < 2; v++) {
              uint32_t a, b, c, d;
              lds128(src + (v * 32 + lane) * 16, a, b, c, d);
              dst[u * 64 + v * 32 + lane] = make_uint4(a, b, c, d);
            }
          }
          __syncwarp();
          if (lane == 0) publish_flag(&g_halo_flag[(ti * 8 + tj) * 8], epoch);
          TSTAMP(15);
        }
        if (ti > 0) {
          if (lane == 0) poll_flag(&g_halo_flag[((ti - 1) * 8 + tj) * 8], epoch);
          __syncwarp();
          const uint4* src = &g_halo[((ti - 1) * 8 + tj) * 256];
#pragma unroll
          for (int v = 0; v < 8; v++) { const uint4 t = ldg_cg(src + v * 32 + lane); sts128(sb + OFF_HALO + (v * 32 + lane) * 16, t.x, t.y, t.z, t.w); }
        } else {
#pragma unroll
          for (int v = 0; v < 8; v++) sts128(sb + OFF_HALO + (v * 32 + lane) * 16, 0u, 0u, 0u, 0u);
        }
        __syncwarp();
        if (lane == 0) mbar_arrive(sb + OFF_BAR + B_HALO * 8);
        TSTAMP(31);
      } else {
#pragma unroll 1
        for (int blk = 0; blk < 3; blk++) {
          mbar_wait(sb + OFF_BAR + (B_PW + 2 * blk + hw) * 8, 0);
          const int c = (ta + 1 + blk) & 3;
          if (lane == 0) publish_flag(&g_part_flag[(((ti * 2 + tb) * 4 + c) * 2 + hw) * 4 + ta], epoch);
          __syncwarp();
        }
        if (lane < 4 && lane != ta) poll_flag(&g_part_flag[(((ti * 2 + tb) * 4 + ta) * 2 + hw) * 4 + lane], epoch);
        __syncwarp();
        if (lane == 0) mbar_arrive(sb + OFF_BAR + (B_PR + hw) * 8);
        TSTAMP(11 + hw);
      }
    }
  } else {
    asm volatile("setmaxnreg.inc.sync.aligned.u32 224;");
    const int p = warp >> 2;
    const int wq = warp & 3;
    const int tw = threadIdx.x & 127;
    const int q = lane & 3;
    uint32_t A[128];
    float acc0[32], acc1[32];
    const uint32_t my_rows = p * 8192 + wq * 2048;
    const uint32_t peer_sb = mapa(sb, tb ^ 1);
    const uint64_t ring_desc = b_desc(sb + OFF_RING);

    {
      const uint32_t tag = (g_launch_cnt[blockIdx.x] + 1) & 3u;
      const int r = 8 * tj + 2 * wq;
      const uint4* src = reinterpret_cast<const uint4*>(prm.x + (size_t)(2 * (64 * ti + r) + p) * 512) + lane;
      const uint4 u0 = __ldg(src), u1 = __ldg(src + 32), w0 = __ldg(src + 128), w1 = __ldg(src + 160);
      const float sh0 = __shfl_sync(0xffffffffu, bf_lo(u0.x), 0), sh1 = __shfl_sync(0xffffffffu, bf_lo(w0.x), 0);
      float s0 = 0.f, q0 = 0.f, s1 = 0.f, q1 = 0.f;
      auto accum = [](uint32_t v, float sh, float& s, float& q) {
        const float a = bf_lo(v) - sh, b = bf_hi(v) - sh;
        s += a + b; q = fmaf(a, a, fmaf(b, b, q));
      };
      accum(u0.x, sh0, s0, q0); accum(u0.y, sh0, s0, q0); accum(u0.z, sh0, s0, q0); accum(u0.w, sh0, s0, q0);
      accum(u1.x, sh0, s0, q0); accum(u1.y, sh0, s0, q0); accum(u1.z, sh0, s0, q0); accum(u1.w, sh0, s0, q0);
      accum(w0.x, sh1, s1, q1); accum(w0.y, sh1, s1, q1); accum(w0.z, sh1, s1, q1); accum(w0.w, sh1, s1, q1);
      accum(w1.x, sh1, s1, q1); accum(w1.y, sh1, s1, q1); accum(w1.z, sh1, s1, q1); accum(w1.w, sh1, s1, q1);
      const bool hi = lane & 16;
      float ss = (hi ? s1 : s0) + __shfl_xor_sync(0xffffffffu, hi ? s0 : s1, 16);
      float qq = (hi ? q1 : q0) + __shfl_xor_sync(0xffffffffu, hi ? q0 : q1, 16);
#pragma unroll
      for (int o = 8; o >= 1; o >>= 1) { ss += __shfl_xor_sync(0xffffffffu, ss, o); qq += __shfl_xor_sync(0xffffffffu, qq, o); }
      if ((lane & 15) == 0) {
        const float m = ss * (1.f / 512.f);
        const float var = fmaxf(qq * (1.f / 512.f) - m * m, 0.f);
        const float mean = (hi ? sh1 : sh0) + m, rstd = 1.f / sqrtf(var + 1e-5f);
        uint32_t* dst = reinterpret_cast<uint32_t*>(g_st) + (ti * 128 + 64 * p + r + (hi ? 1 : 0)) * 2;
        asm volatile("st.relaxed.gpu.global.v2.u32 [%0], {%1, %2};" ::"l"(dst), "r"((__float_as_uint(mean) & ~3u) | tag), "r"((__float_as_uint(rstd) & ~3u) | tag) : "memory");
      }
    }
    auto load_x_block = [&](auto KB) {
      constexpr int kb = decltype(KB)::value;
      mbar_wait(sb + OFF_BAR + (B_X + 2 * kb + p) * 8, 0);
      if (warp == 0) TSTAMP(40 + kb);
#pragma unroll
      for (int ks = 0; ks < 4; ks++)
        ldsm4(frag_addr(sb + OFF_U + kb * 16384 + my_rows, lane, ks), A[16 * kb + 4 * ks], A[16 * kb + 4 * ks + 1], A[16 * kb + 4 * ks + 2], A[16 * kb + 4 * ks + 3]);
    };

    if (warp == 0) TSTAMP(16);
    load_x_block(IC(0));
    if (warp == 0) TSTAMP(17);
    auto j0_step = [&](auto KB) {
      constexpr int kb = decltype(KB)::value;
      issue_tile<2 * kb, 16 * kb, 4, kb == 0, false>(acc0, A, sb, ring_desc);
      issue_tile<2 * kb + 1, 16 * kb, 4, kb == 0, false>(acc1, A, sb, ring_desc);
      if (warp == 0) TSTAMP(48 + kb);
      if constexpr (kb < 7) load_x_block(IC(kb + 1));
      if constexpr (kb < 7) { wg_wait<2>(); release_tile<2 * kb - 1>(sb, lane); }
    };
    j0_step(IC(0)); j0_step(IC(1)); j0_step(IC(2)); j0_step(IC(3));
    j0_step(IC(4)); j0_step(IC(5)); j0_step(IC(6));
    if (warp == 0) TSTAMP(33);
    asm volatile("barrier.cluster.wait.aligned;" ::: "memory");
    if (lane == 0) mbar_arrive_remote(peer_sb + OFF_BAR + B_PEERX * 8);
    j0_step(IC(7));
    if (warp == 0) TSTAMP(18);
    const uint32_t cs_lane = sb + OFF_CS + (2 * q) * 4;
    RowStats st;
    auto epi_to_unit = [&](const float (&acc)[32], int g, int unit, int cs_col, float r0, float r1) {
      uint32_t p0, p1, p2, p3;
      epi16<false>(acc, g, cs_lane + cs_col * 4, st, r0, r1, p0, p1, p2, p3);
      stsm4(frag_addr(sb + OFF_U + unit * 16384 + my_rows, lane, g), p0, p1, p2, p3);
    };
    wg_wait<1>();
    release_tile<13>(sb, lane);
    fence_acc(acc0);
    mbar_wait(sb + OFF_BAR + B_CS * 8, 0);
    if (warp == 0) TSTAMP(37);
    {
      const float2 a = lds64f(sb + OFF_ST + (64 * p + 16 * wq + (lane >> 2)) * 8), b = lds64f(sb + OFF_ST + (64 * p + 16 * wq + (lane >> 2) + 8) * 8);
      st.mean0 = a.x; st.r0 = a.y; st.mean1 = b.x; st.r1 = b.y;
    }
#pragma unroll
    for (int g = 0; g < 4; g++) epi_to_unit(acc0, g, 0, 0, st.r0 * 0.25f, st.r1 * 0.25f);
    if (warp == 0) TSTAMP(19);

    issue_tile<16, 0, 4, true, false>(acc0, A, sb, ring_desc);
    wg_wait<1>(); release_tile<15>(sb, lane);
    fence_acc(acc1);
    epi_to_unit(acc1, 0, 1, 64, st.r0, st.r1); epi_to_unit(acc1, 1, 1, 64, st.r0, st.r1);
    issue_tile<17, 16, 4, false, false>(acc0, A, sb, ring_desc);
    epi_to_unit(acc1, 2, 1, 64, st.r0, st.r1); epi_to_unit(acc1, 3, 1, 64, st.r0, st.r1);
    issue_tile<18, 32, 4, false, false>(acc0, A, sb, ring_desc); wg_wait<2>();
    issue_tile<19, 48, 4, false, false>(acc0, A, sb, ring_desc); retire<19, LAG>(sb, lane);
    issue_tile<20, 64, 4, false, false>(acc0, A, sb, ring_desc); retire<20, LAG>(sb, lane);
    issue_tile<21, 80, 4, false, false>(acc0, A, sb, ring_desc); retire<21, LAG>(sb, lane);
    issue_tile<22, 96, 4, false, false>(acc0, A, sb, ring_desc); retire<22, LAG>(sb, lane);
    issue_tile<23, 112, 4, false, false>(acc0, A, sb, ring_desc); retire<23, LAG>(sb, lane);
    if (warp == 0) TSTAMP(27);

    issue_tile<24, 0, 4, true, false>(acc1, A, sb, ring_desc); retire<24, LAG>(sb, lane);
    issue_tile<25, 16, 4, false, false>(acc1, A, sb, ring_desc); retire<25, LAG>(sb, lane);
    fence_acc(acc0);
    epi_to_unit(acc0, 0, 2, 128, st.r0, st.r1); epi_to_unit(acc0, 1, 2, 128, st.r0, st.r1);
    issue_tile<26, 32, 4, false, false>(acc1, A, sb, ring_desc); retire<26, LAG>(sb, lane);
    epi_to_unit(acc0, 2, 2, 128, st.r0, st.r1); epi_to_unit(acc0, 3, 2, 128, st.r0, st.r1);
    __syncwarp();
    if (lane == 0) mbar_arrive(sb + OFF_BAR + B_QKV * 8);
    if (warp == 0) TSTAMP(20);
    issue_tile<27, 48, 4, false, false>(acc1, A, sb, ring_desc); retire<27, LAG>(sb, lane);
    issue_tile<28, 64, 4, false, false>(acc1, A, sb, ring_desc); retire<28, LAG>(sb, lane);
    issue_tile<29, 80, 4, false, false>(acc1, A, sb, ring_desc); retire<29, LAG>(sb, lane);
    issue_tile<30, 96, 4, false, false>(acc1, A, sb, ring_desc); retire<30, LAG>(sb, lane);
    issue_tile<31, 112, 4, false, false>(acc1, A, sb, ring_desc); retire<31, LAG>(sb, lane);
    if (warp == 0) TSTAMP(28);

    const uint32_t thr16 = p * 8192 + tw * 16;
    issue_tile<32, 0, 4, true, false>(acc0, A, sb, ring_desc); retire<32, LAG>(sb, lane);
    issue_tile<33, 16, 4, false, false>(acc0, A, sb, ring_desc); retire<33, LAG>(sb, lane);
    fence_acc(acc1);
    mbar_wait_cluster(sb + OFF_BAR + B_PEERX * 8, 0);
    auto epi_f0 = [&](int g) {
      uint32_t p0, p1, p2, p3;
      epi16<true>(acc1, g, cs_lane + 192 * 4, st, st.r0, st.r1, p0, p1, p2, p3);
      sts128(sb + OFF_U + 3 * 16384 + thr16 + g * 2048, p0, p1, p2, p3);
      st_async4(peer_sb + OFF_U + 5 * 16384 + thr16 + g * 2048, peer_sb + OFF_BAR + (B_LAND + 2 + p) * 8, p0, p1, p2, p3);
    };
    epi_f0(0); epi_f0(1);
    issue_tile<34, 32, 4, false, false>(acc0, A, sb, ring_desc); retire<34, LAG>(sb, lane);
    epi_f0(2); epi_f0(3);
    issue_tile<35, 48, 4, false, false>(acc0, A, sb, ring_desc); retire<35, LAG>(sb, lane);
    issue_tile<36, 64, 4, false, false>(acc0, A, sb, ring_desc); retire<36, LAG>(sb, lane);
    issue_tile<37, 80, 4, false, false>(acc0, A, sb, ring_desc); retire<37, LAG>(sb, lane);
    issue_tile<38, 96, 4, false, false>(acc0, A, sb, ring_desc); retire<38, LAG>(sb, lane);
    issue_tile<39, 112, 4, false, false>(acc0, A, sb, ring_desc); retire<39, LAG>(sb, lane);
    if (warp == 0) TSTAMP(21);

    wg_wait<0>();
    release_tile<39>(sb, lane);
    if (wq == 0) mbar_wait(sb + OFF_BAR + B_HALO * 8, 0);
    if (warp == 0) TSTAMP(34);
    {
        const uint32_t Qt = sb + OFF_U, Kt = sb + OFF_U + 16384, Vt = sb + OFF_U + 32768;
        const uint32_t Hk = sb + OFF_HALO, Hv = sb + OFF_HALO + 2048;
        const int g = lane >> 2;
        const uint32_t r0 = 64 * p + 16 * wq;
        const bool halo = (wq == 0);
        const bool first = halo && (ti == 0);
        const int m = lane >> 3, rr = lane & 7;
        const uint32_t kA = ((m < 2 && halo) ? (Hk + p * 1024 + rr * 128) : (Kt + (r0 - 8 + 8 * (m >> 1) + rr) * 128)) + (((m & 1) ^ rr) << 4);
        const uint32_t kB = Kt + (r0 + 8 + rr) * 128 + (((m & 1) ^ rr) << 4);
        const uint32_t vA = (((m & 1) == 0 && halo) ? (Hv + p * 1024 + rr * 128) : (Vt + (r0 - 8 + 8 * (m & 1) + rr) * 128)) + (((m >> 1) ^ rr) << 4);
        const uint32_t vB = Vt + (r0 + 8 + rr) * 128 + (((m & 1) ^ rr) << 4);
        const uint32_t qA = Qt + (r0 + (lane & 15)) * 128 + (((lane >> 4) ^ rr) << 4);
        const bool u0 = (2 * q) <= g, u1 = (2 * q + 1) <= g;
        float a0[4], a1[4], b0[4], b1[4];
        {
          uint32_t fq[2][4], fk[2][6];
          ldsm4(qA, fq[0][0], fq[0][1], fq[0][2], fq[0][3]);
          ldsm4(kA, fk[0][0], fk[0][1], fk[0][2], fk[0][3]);
          ldsm2(kB, fk[0][4], fk[0][5]);
#pragma unroll
          for (int h = 0; h < 4; h++) {
            const int c = h & 1, n = c ^ 1;
            if (h < 3) {
              ldsm4(qA ^ ((h + 1) << 5), fq[n][0], fq[n][1], fq[n][2], fq[n][3]);
              ldsm4(kA ^ ((h + 1) << 5), fk[n][0], fk[n][1], fk[n][2], fk[n][3]);
              ldsm2(kB ^ ((h + 1) << 5), fk[n][4], fk[n][5]);
            }
            float s0[4] = {0.f, 0.f, 0.f, 0.f}, s1[4] = {0.f, 0.f, 0.f, 0.f}, s2[4] = {0.f, 0.f, 0.f, 0.f};
            mma16816(s0, fq[c][0], fq[c][1], fq[c][2], fq[c][3], fk[c][0], fk[c][1]);
            mma16816(s1, fq[c][0], fq[c][1], fq[c][2], fq[c][3], fk[c][2], fk[c][3]);
            mma16816(s2, fq[c][0], fq[c][1], fq[c][2], fq[c][3], fk[c][4], fk[c][5]);
            a0[h] = u0 ? s1[0] : (first ? -INFINITY : s0[0]);
            a1[h] = u1 ? s1[1] : (first ? -INFINITY : s0[1]);
            b0[h] = u0 ? s2[2] : s1[2];
            b1[h] = u1 ? s2[3] : s1[3];
          }
        }
        uint32_t fv[2][6];
        ldsm4t(vA, fv[0][0], fv[0][1], fv[0][2], fv[0][3]);
        ldsm2t(vB, fv[0][4], fv[0][5]);
        float ma[4], mb[4];
#pragma unroll
        for (int h = 0; h < 4; h++) { ma[h] = fmaxf(a0[h], a1[h]); mb[h] = fmaxf(b0[h], b1[h]); }
#pragma unroll
        for (int x = 1; x <= 2; x <<= 1) {
          float ta_[4], tb_[4];
#pragma unroll
          for (int h = 0; h < 4; h++) { ta_[h] = __shfl_xor_sync(0xffffffffu, ma[h], x); tb_[h] = __shfl_xor_sync(0xffffffffu, mb[h], x); }
#pragma unroll
          for (int h = 0; h < 4; h++) { ma[h] = fmaxf(ma[h], ta_[h]); mb[h] = fmaxf(mb[h], tb_[h]); }
        }
        uint32_t P0[4], P2[4], P3[4], P5[4];
        constexpr float LOG2E = 1.4426950408889634f;
#pragma unroll
        for (int h = 0; h < 4; h++) {
          const float ea0 = ex2((a0[h] - ma[h]) * LOG2E), ea1 = ex2((a1[h] - ma[h]) * LOG2E);
          const float eb0 = ex2((b0[h] - mb[h]) * LOG2E), eb1 = ex2((b1[h] - mb[h]) * LOG2E);
          P0[h] = pack_bf16(u0 ? 0.f : ea0, u1 ? 0.f : ea1);
          P2[h] = pack_bf16(u0 ? ea0 : 0.f, u1 ? ea1 : 0.f);
          P3[h] = pack_bf16(u0 ? 0.f : eb0, u1 ? 0.f : eb1);
          P5[h] = pack_bf16(u0 ? eb0 : 0.f, u1 ? eb1 : 0.f);
        }
        constexpr uint32_t ONES = 0x3F803F80u;
#pragma unroll
        for (int h = 0; h < 4; h++) {
          const int c = h & 1, n = c ^ 1;
          if (h < 3) {
            ldsm4t(vA ^ ((h + 1) << 5), fv[n][0], fv[n][1], fv[n][2], fv[n][3]);
            ldsm2t(vB ^ ((h + 1) << 5), fv[n][4], fv[n][5]);
          }
          float o0[4] = {0.f, 0.f, 0.f, 0.f}, o1[4] = {0.f, 0.f, 0.f, 0.f}, rs[4] = {0.f, 0.f, 0.f, 0.f};
          mma16816(rs, P0[h], 0u, P2[h], P3[h], ONES, ONES);
          mma16816(o0, P0[h], 0u, P2[h], P3[h], fv[c][0], fv[c][1]);
          mma16816(o1, P0[h], 0u, P2[h], P3[h], fv[c][2], fv[c][3]);
          mma1688(rs, 0u, P5[h], ONES);
          mma1688(o0, 0u, P5[h], fv[c][4]);
          mma1688(o1, 0u, P5[h], fv[c][5]);
          const float ia = __fdividef(1.f, rs[0]), ib = __fdividef(1.f, rs[2]);
          stsm4(qA ^ (h << 5), pack_bf16(o0[0] * ia, o0[1] * ia), pack_bf16(o0[2] * ib, o0[3] * ib),
                pack_bf16(o1[0] * ia, o1[1] * ia), pack_bf16(o1[2] * ib, o1[3] * ib));
        }
          }
    __syncwarp();
    if (lane == 0) mbar_arrive(sb + OFF_BAR + B_O * 8);
    if (warp == 0) TSTAMP(35);

    issue_tile<40, 0, 4, true, true>(acc1, A, sb, ring_desc);
    issue_tile<41, 16, 4, false, true>(acc1, A, sb, ring_desc);
    issue_tile<42, 32, 4, false, true>(acc1, A, sb, ring_desc); retire<42, LAG>(sb, lane);
#pragma unroll
    for (int g = 0; g < 4; g++) {
      ldsm4(frag_addr(sb + OFF_U + my_rows, lane, g), A[4 * g], A[4 * g + 1], A[4 * g + 2], A[4 * g + 3]);
      st_async4(peer_sb + OFF_U + 4 * 16384 + thr16 + g * 2048, peer_sb + OFF_BAR + (B_LAND + 0 + p) * 8, A[4 * g], A[4 * g + 1], A[4 * g + 2], A[4 * g + 3]);
    }
    issue_tile<43, 48, 4, false, true>(acc1, A, sb, ring_desc); retire<43, LAG>(sb, lane);
#pragma unroll
    for (int g = 0; g < 4; g++) lds128(sb + OFF_U + 3 * 16384 + thr16 + g * 2048, A[16 + 4 * g], A[17 + 4 * g], A[18 + 4 * g], A[19 + 4 * g]);
    issue_tile<44, 64, 4, false, true>(acc1, A, sb, ring_desc); retire<44, LAG>(sb, lane);
    fence_acc(acc0);
#pragma unroll
    for (int g = 0; g < 4; g++) {
      epi16<true>(acc0, g, cs_lane + 256 * 4, st, st.r0, st.r1, A[32 + 4 * g], A[33 + 4 * g], A[34 + 4 * g], A[35 + 4 * g]);
      st_async4(peer_sb + OFF_U + 6 * 16384 + thr16 + g * 2048, peer_sb + OFF_BAR + (B_LAND + 4 + p) * 8, A[32 + 4 * g], A[33 + 4 * g], A[34 + 4 * g], A[35 + 4 * g]);
    }
    issue_tile<45, 80, 4, false, true>(acc1, A, sb, ring_desc); retire<45, LAG>(sb, lane);
    mbar_wait_cluster(sb + OFF_BAR + (B_LAND + 0 + p) * 8, 0);
#pragma unroll
    for (int g = 0; g < 4; g++) lds128(sb + OFF_U + 4 * 16384 + thr16 + g * 2048, A[48 + 4 * g], A[49 + 4 * g], A[50 + 4 * g], A[51 + 4 * g]);
    issue_tile<46, 96, 4, false, true>(acc1, A, sb, ring_desc); retire<46, LAG>(sb, lane);
    mbar_wait_cluster(sb + OFF_BAR + (B_LAND + 2 + p) * 8, 0);
#pragma unroll
    for (int g = 0; g < 4; g++) lds128(sb + OFF_U + 5 * 16384 + thr16 + g * 2048, A[64 + 4 * g], A[65 + 4 * g], A[66 + 4 * g], A[67 + 4 * g]);
    issue_tile<47, 112, 4, false, true>(acc1, A, sb, ring_desc); retire<47, LAG>(sb, lane);
    if (warp == 0) TSTAMP(22);

    issue_tile<48, 0, 4, true, false>(acc0, A, sb, ring_desc); retire<48, LAG>(sb, lane);
    issue_tile<49, 48, 4, false, false>(acc0, A, sb, ring_desc); retire<49, LAG>(sb, lane);
    fence_acc(acc1);
#pragma unroll
    for (int g = 0; g < 3; g++) {
      epi16<true>(acc1, g, cs_lane + 320 * 4, st, st.r0, st.r1, A[96 + 4 * g], A[97 + 4 * g], A[98 + 4 * g], A[99 + 4 * g]);
      st_async4(peer_sb + OFF_U + 7 * 16384 + thr16 + g * 2048, peer_sb + OFF_BAR + (B_LAND + 6 + p) * 8, A[96 + 4 * g], A[97 + 4 * g], A[98 + 4 * g], A[99 + 4 * g]);
    }
    issue_tile<50, 16, 4, false, false>(acc0, A, sb, ring_desc); retire<50, LAG>(sb, lane);
    mbar_wait_cluster(sb + OFF_BAR + (B_LAND + 4 + p) * 8, 0);
#pragma unroll
    for (int g = 0; g < 4; g++) lds128(sb + OFF_U + 6 * 16384 + thr16 + g * 2048, A[80 + 4 * g], A[81 + 4 * g], A[82 + 4 * g], A[83 + 4 * g]);
    issue_tile<51, 32, 4, false, false>(acc0, A, sb, ring_desc); retire<51, LAG>(sb, lane);
    issue_tile<52, 64, 4, false, false>(acc0, A, sb, ring_desc); retire<52, LAG>(sb, lane);
    issue_tile<53, 80, 4, false, false>(acc0, A, sb, ring_desc); retire<53, LAG>(sb, lane);
    mbar_wait_cluster(sb + OFF_BAR + (B_LAND + 6 + p) * 8, 0);
#pragma unroll
    for (int g = 0; g < 3; g++) lds128(sb + OFF_U + 7 * 16384 + thr16 + g * 2048, A[112 + 4 * g], A[113 + 4 * g], A[114 + 4 * g], A[115 + 4 * g]);
    issue_tile<54, 96, 3, false, false>(acc0, A, sb, ring_desc); retire<54, LAG>(sb, lane);
    issue_tile<55, 112, 3, false, false>(acc0, A, sb, ring_desc); retire<55, LAG>(sb, lane);
    if (warp == 0) TSTAMP(23);

    auto store_partial = [&](float (&acc)[32], int blk) {
      fence_acc(acc);
      const int c = (ta + 1 + blk) & 3;
      uint4* dst = &g_part[(((((ti * 2 + tb) * 4 + c) * 4 + ta) * 2 + p) * 512) + tw];
#pragma unroll
      for (int v = 0; v < 4; v++)
        dst[v * 128] = make_uint4(pack_bf16(acc[8 * v], acc[8 * v + 1]), pack_bf16(acc[8 * v + 2], acc[8 * v + 3]),
                                  pack_bf16(acc[8 * v + 4], acc[8 * v + 5]), pack_bf16(acc[8 * v + 6], acc[8 * v + 7]));
      __syncwarp();
      if (lane == 0) mbar_arrive(sb + OFF_BAR + (B_PW + 2 * blk + p) * 8);
    };
#define P2_BLOCK(N0, ACC, PREV, PBLK)                                                         \
    issue_tile<N0 + 0, 0, 4, true, false>(ACC, A, sb, ring_desc); retire<N0 + 0, LAG>(sb, lane);           \
    issue_tile<N0 + 1, 48, 4, false, false>(ACC, A, sb, ring_desc); retire<N0 + 1, LAG>(sb, lane);         \
    store_partial(PREV, PBLK);                                                                  \
    issue_tile<N0 + 2, 16, 4, false, false>(ACC, A, sb, ring_desc); retire<N0 + 2, LAG>(sb, lane);         \
    issue_tile<N0 + 3, 32, 4, false, false>(ACC, A, sb, ring_desc); retire<N0 + 3, LAG>(sb, lane);         \
    issue_tile<N0 + 4, 64, 4, false, false>(ACC, A, sb, ring_desc); retire<N0 + 4, LAG>(sb, lane);         \
    issue_tile<N0 + 5, 80, 4, false, false>(ACC, A, sb, ring_desc); retire<N0 + 5, LAG>(sb, lane);         \
    issue_tile<N0 + 6, 96, 3, false, false>(ACC, A, sb, ring_desc); retire<N0 + 6, LAG>(sb, lane);         \
    issue_tile<N0 + 7, 112, 3, false, false>(ACC, A, sb, ring_desc); retire<N0 + 7, LAG>(sb, lane);
    P2_BLOCK(56, acc1, acc0, 0)
    if (warp == 0) TSTAMP(29);
    P2_BLOCK(64, acc0, acc1, 1)
    if (warp == 0) TSTAMP(30);
    P2_BLOCK(72, acc1, acc0, 2)
    if (warp == 0) TSTAMP(24);

    uint32_t res[16];
    mbar_wait(sb + OFF_BAR + (B_RES + p) * 8, 0);
#pragma unroll
    for (int g = 0; g < 4; g++) ldsm4(frag_addr(sb + OFF_U + 16384 + my_rows, lane, g), res[4 * g], res[4 * g + 1], res[4 * g + 2], res[4 * g + 3]);
    mbar_wait(sb + OFF_BAR + (B_PR + p) * 8, 0);
    if (warp == 0) TSTAMP(25);
    {
      const uint4* src = &g_part[((((ti * 2 + tb) * 4 + ta) * 4) * 2 + p) * 512 + tw];
      uint4 pv[3][4];
#pragma unroll
      for (int s = 0; s < 3; s++) {
        const int sa = (ta + 1 + s) & 3;
#pragma unroll
        for (int v = 0; v < 4; v++) pv[s][v] = ldg_cg(src + sa * 1024 + v * 128);
      }
      wg_wait<0>();
      fence_acc(acc1);
      if (warp == 0) TSTAMP(39);
#pragma unroll
      for (int v = 0; v < 4; v++) {
        float y[8];
#pragma unroll
        for (int e = 0; e < 4; e++) {
          const uint32_t r = res[4 * v + e];
          const uint32_t a = e == 0 ? pv[0][v].x : e == 1 ? pv[0][v].y : e == 2 ? pv[0][v].z : pv[0][v].w;
          const uint32_t b = e == 0 ? pv[1][v].x : e == 1 ? pv[1][v].y : e == 2 ? pv[1][v].z : pv[1][v].w;
          const uint32_t c = e == 0 ? pv[2][v].x : e == 1 ? pv[2][v].y : e == 2 ? pv[2][v].z : pv[2][v].w;
          y[2 * e] = ((acc1[8 * v + 2 * e] + bf_lo(a)) + (bf_lo(b) + bf_lo(c))) + bf_lo(r);
          y[2 * e + 1] = ((acc1[8 * v + 2 * e + 1] + bf_hi(a)) + (bf_hi(b) + bf_hi(c))) + bf_hi(r);
        }
        stsm4(frag_addr(sb + OFF_U + 2 * 16384 + my_rows, lane, v), pack_bf16(y[0], y[1]), pack_bf16(y[2], y[3]), pack_bf16(y[4], y[5]), pack_bf16(y[6], y[7]));
      }
    }
    __syncwarp();
    if (warp == 0) TSTAMP(38);
    {
      uint8_t* outp = reinterpret_cast<uint8_t*>(prm.out) + (size_t)(2 * (64 * ti + 16 * wq + (lane >> 3)) + p) * 1024 + (256 * tb + 64 * ta) * 2 + (lane & 7) * 16;
#pragma unroll
      for (int it = 0; it < 4; it++) {
        const int r = 4 * it + (lane >> 3);
        uint32_t v0, v1, v2, v3;
        lds128(sb + OFF_U + 2 * 16384 + my_rows + r * 128 + (((lane & 7) ^ (r & 7)) << 4), v0, v1, v2, v3);
        *reinterpret_cast<uint4*>(outp + (size_t)it * 8 * 1024) = make_uint4(v0, v1, v2, v3);
      }
    }
    if (warp == 0) TSTAMP(26);
  }
}

typedef CUresult (*EncodeFn)(CUtensorMap*, CUtensorMapDataType, cuuint32_t, void*, const cuuint64_t*, const cuuint64_t*,
                             const cuuint32_t*, const cuuint32_t*, CUtensorMapInterleave, CUtensorMapSwizzle,
                             CUtensorMapL2promotion, CUtensorMapFloatOOBfill);

CUtensorMap make_map(EncodeFn fn, const void* ptr, uint64_t rows, uint64_t cols) {
  CUtensorMap m;
  cuuint64_t dims[2] = {cols, rows};
  cuuint64_t strides[1] = {cols * 2};
  cuuint32_t box[2] = {64, 64};
  cuuint32_t es[2] = {1, 1};
  fn(&m, CU_TENSOR_MAP_DATA_TYPE_BFLOAT16, 2, const_cast<void*>(ptr), dims, strides, box, es, CU_TENSOR_MAP_INTERLEAVE_NONE,
     CU_TENSOR_MAP_SWIZZLE_128B, CU_TENSOR_MAP_L2_PROMOTION_L2_128B, CU_TENSOR_MAP_FLOAT_OOB_FILL_NONE);
  return m;
}

}

extern "C" void kernel_launch(void* const* d_in, const int* in_sizes, int n_in, void* d_out, int out_size) {
  (void)in_sizes; (void)n_in; (void)out_size;
  const __nv_bfloat16* x = (const __nv_bfloat16*)d_in[0];
  const __nv_bfloat16* wqkv = (const __nv_bfloat16*)d_in[1];
  const __nv_bfloat16* wo = (const __nv_bfloat16*)d_in[2];
  const __nv_bfloat16* w1 = (const __nv_bfloat16*)d_in[4];
  const __nv_bfloat16* w2 = (const __nv_bfloat16*)d_in[5];

  static EncodeFn encode = nullptr;
  if (!encode) {
    void* fn = nullptr;
    cudaDriverEntryPointQueryResult qr;
    cudaGetDriverEntryPoint("cuTensorMapEncodeTiled", &fn, cudaEnableDefault, &qr);
    encode = (EncodeFn)fn;
    cudaFuncSetAttribute(fused_kernel, cudaFuncAttributeMaxDynamicSharedMemorySize, SMEM_BYTES);
  }
  const CUtensorMap tmX = make_map(encode, x, 1024, 1024);
  const CUtensorMap tmWqkv = make_map(encode, wqkv, 512, 1536);
  const CUtensorMap tmW1 = make_map(encode, w1, 512, kF);
  const CUtensorMap tmWo = make_map(encode, wo, 512, 512);
  const CUtensorMap tmW2 = make_map(encode, w2, kF, 512);
  Params prm{x, wqkv, w1, (__nv_bfloat16*)d_out};

  cudaLaunchConfig_t cfg = {};
  cfg.gridDim = dim3(128);
  cfg.blockDim = dim3(384);
  cfg.dynamicSmemBytes = SMEM_BYTES;
  cfg.stream = cudaStreamPerThread;
  cudaLaunchAttribute at[1];
  at[0].id = cudaLaunchAttributeClusterDimension;
  at[0].val.clusterDim.x = 2; at[0].val.clusterDim.y = 1; at[0].val.clusterDim.z = 1;
  cfg.attrs = at; cfg.numAttrs = 1;
  cudaLaunchKernelEx(&cfg, fused_kernel, tmX, tmWqkv, tmW1, tmWo, tmW2, prm);
}
```

```cpp
#include <cuda_runtime.h>
#include <cuda_bf16.h>
#include <cuda.h>
#include <stdint.h>
#include <type_traits>

namespace {

constexpr int kS = 2048, kD = 512, kF = 1376;
constexpr int kFS = 176;
constexpr int kCS = 192 + kFS;
constexpr int NTILE = 80;
constexpr int NDS = NTILE / 2;
constexpr int LAG = 2;

constexpr uint32_t OFF_U = 0;
constexpr uint32_t OFF_HALO = 13 * 16384;
constexpr uint32_t OFF_CS = OFF_HALO + 4096;
constexpr uint32_t OFF_ST = OFF_CS + 512;
constexpr uint32_t OFF_TAG = OFF_ST + 1024;
constexpr uint32_t OFF_BAR = OFF_TAG + 16;
constexpr int NDS0 = 3;
constexpr int B_FULL = 0, B_EMPTY = B_FULL + NDS, B_X = B_EMPTY + NDS  , B_LAND = B_X + 16  , B_RES = B_LAND + 8  ,
              B_QKV = B_RES + 2, B_O = B_QKV + 1, B_CS = B_O + 1, B_PEERX = B_CS + 1, B_PEERX2 = B_PEERX + 1, B_HALO = B_PEERX2 + 1,
              B_DONE = B_HALO + 1, B_LAG = B_DONE + 1  , B_XC = B_LAG + 2, B_U03 = B_XC + 1, B_LF = B_U03 + 1, B_COUNT = B_LF + 1;
enum : int { U0 = 0, U1, U2, U3, U4, U5, U6, U7, R0, R1, R2, R3, R4 };
__host__ __device__ constexpr int ds_buf(int m) {
  constexpr int t[NDS] = {R0, R1, R2, R3, R4, R0, R1, R2,
                          R3, R4, U4, U6, U7, R0, R1, R2, R3, R4, U4, U6,
                          R0, R1, R2, R3,
                          R4, U1, U2, R0, R1, U0, R2, R3, R4, U1, U2, U4, U5, U6, R0, R1};
  return t[m];
}
__host__ __device__ constexpr int ds_wait(int m) {
  if (m == 10 || m == 11 || m == 12) return B_XC;
  if (m == 25 || m == 26) return B_O;
  if (m == 29) return B_U03;
  if (m == 35 || m == 36 || m == 37) return B_LF;
  for (int k = m - 1; k >= 0; k--) if (ds_buf(k) == ds_buf(m)) return B_EMPTY + k;
  return -1;
}
__host__ __device__ constexpr bool ds_release_needed(int m) {
  for (int k = m + 1; k < NDS; k++) if (ds_wait(k) == B_EMPTY + m) return true;
  return false;
}
__host__ __device__ constexpr uint64_t ds_word(int w) {
  uint64_t v = 0;
  for (int i = 0; i < 4; i++) v |= (uint64_t)(ds_buf(4 * w + i) | ((ds_wait(4 * w + i) & 0xff) << 4)) << (16 * i);
  return v;
}
constexpr uint32_t SMEM_USED = OFF_BAR + B_COUNT * 8;
constexpr uint32_t SMEM_BYTES = SMEM_USED + 1024;

constexpr int SPIN_LIMIT = 1 << 22;

__device__ uint4 g_st[16 * 64];
__device__ uint4 g_halo[16 * 8 * 512];
__device__ uint4 g_part[16 * 2 * 4 * 4 * 2 * 512];
__device__ uint32_t g_launch_cnt[128];

__device__ __forceinline__ uint32_t smem_u32(const void* p) { return (uint32_t)__cvta_generic_to_shared(p); }
__device__ __forceinline__ void mbar_init(uint32_t bar, uint32_t count) {
  asm volatile("mbarrier.init.shared::cta.b64 [%0], %1;" ::"r"(bar), "r"(count));
}
__device__ __forceinline__ void mbar_expect_tx(uint32_t bar, uint32_t bytes) {
  asm volatile("mbarrier.arrive.expect_tx.shared::cta.b64 _, [%0], %1;" ::"r"(bar), "r"(bytes) : "memory");
}
__device__ __forceinline__ void mbar_arrive(uint32_t bar) {
  asm volatile("mbarrier.arrive.shared::cta.b64 _, [%0];" ::"r"(bar) : "memory");
}
__device__ __forceinline__ void mbar_arrive_remote(uint32_t bar_cluster) {
  asm volatile("mbarrier.arrive.shared::cluster.b64 _, [%0];" ::"r"(bar_cluster) : "memory");
}
__device__ __forceinline__ void mbar_wait(uint32_t bar, uint32_t parity) {
  asm volatile("{\n.reg .pred p, q;\n.reg .u32 c;\nmov.u32 c, 0;\n"
               "WAIT_LOOP:\nmbarrier.try_wait.parity.shared::cta.b64 p, [%0], %1;\n@p bra WAIT_DONE;\n"
               "add.u32 c, c, 1;\nsetp.gt.u32 q, c, %2;\n@q trap;\nbra WAIT_LOOP;\nWAIT_DONE:\n}\n"
               ::"r"(bar), "r"(parity), "n"(SPIN_LIMIT) : "memory");
}
__device__ __forceinline__ void mbar_wait_cluster(uint32_t bar, uint32_t parity) {
  asm volatile("{\n.reg .pred p, q;\n.reg .u32 c;\nmov.u32 c, 0;\n"
               "WAIT_LOOP:\nmbarrier.try_wait.parity.acquire.cluster.shared::cta.b64 p, [%0], %1;\n@p bra WAIT_DONE;\n"
               "add.u32 c, c, 1;\nsetp.gt.u32 q, c, %2;\n@q trap;\nbra WAIT_LOOP;\nWAIT_DONE:\n}\n"
               ::"r"(bar), "r"(parity), "n"(SPIN_LIMIT) : "memory");
}
__device__ __forceinline__ void mbar_spin(uint32_t bar, uint32_t parity) {
  asm volatile("{\n.reg .pred p;\nWAIT_LOOP:\nmbarrier.try_wait.parity.shared::cta.b64 p, [%0], %1;\n@!p bra WAIT_LOOP;\n}\n" ::"r"(bar), "r"(parity) : "memory");
}
__device__ __forceinline__ void mbar_spin_cluster(uint32_t bar, uint32_t parity) {
  asm volatile("{\n.reg .pred p;\nWAIT_LOOP:\nmbarrier.try_wait.parity.acquire.cluster.shared::cta.b64 p, [%0], %1;\n@!p bra WAIT_LOOP;\n}\n" ::"r"(bar), "r"(parity) : "memory");
}
__device__ __forceinline__ bool elect_one() {
  uint32_t pred;
  asm volatile("{\n.reg .pred p;\nelect.sync _|p, 0xffffffff;\nselp.u32 %0, 1, 0, p;\n}\n" : "=r"(pred));
  return pred;
}
__device__ __forceinline__ void tma_load(uint32_t dst, const CUtensorMap* tm, uint32_t bar, int c0, int c1) {
  asm volatile("cp.async.bulk.tensor.2d.shared::cluster.global.mbarrier::complete_tx::bytes [%0], [%1, {%3, %4}], [%2];"
               ::"r"(dst), "l"(tm), "r"(bar), "r"(c0), "r"(c1) : "memory");
}
__device__ __forceinline__ void tma_prefetch(const CUtensorMap* tm, int c0, int c1) {
  asm volatile("cp.async.bulk.prefetch.tensor.2d.L2.global [%0, {%1, %2}];" ::"l"(tm), "r"(c0), "r"(c1) : "memory");
}
__device__ __forceinline__ void prefetch_tmap(const CUtensorMap* tm) {
  asm volatile("prefetch.tensormap [%0];" ::"l"(tm) : "memory");
}
__device__ __forceinline__ uint32_t mapa(uint32_t addr, uint32_t rank) {
  uint32_t r;
  asm("mapa.shared::cluster.u32 %0, %1, %2;" : "=r"(r) : "r"(addr), "r"(rank));
  return r;
}
__device__ __forceinline__ void st_async4(uint32_t addr, uint32_t bar, uint32_t a, uint32_t b, uint32_t c, uint32_t d) {
  asm volatile("st.async.weak.shared::cluster.mbarrier::complete_tx::bytes.v4.b32 [%0], {%2, %3, %4, %5}, [%1];"
               ::"r"(addr), "r"(bar), "r"(a), "r"(b), "r"(c), "r"(d) : "memory");
}
__device__ __forceinline__ void ldsm4(uint32_t addr, uint32_t& a, uint32_t& b, uint32_t& c, uint32_t& d) {
  asm volatile("ldmatrix.sync.aligned.m8n8.x4.shared.b16 {%0, %1, %2, %3}, [%4];"
               : "=r"(a), "=r"(b), "=r"(c), "=r"(d) : "r"(addr) : "memory");
}
__device__ __forceinline__ void ldsm2(uint32_t addr, uint32_t& a, uint32_t& b) {
  asm volatile("ldmatrix.sync.aligned.m8n8.x2.shared.b16 {%0, %1}, [%2];" : "=r"(a), "=r"(b) : "r"(addr) : "memory");
}
__device__ __forceinline__ void ldsm4t(uint32_t addr, uint32_t& a, uint32_t& b, uint32_t& c, uint32_t& d) {
  asm volatile("ldmatrix.sync.aligned.m8n8.x4.trans.shared.b16 {%0, %1, %2, %3}, [%4];"
               : "=r"(a), "=r"(b), "=r"(c), "=r"(d) : "r"(addr) : "memory");
}
__device__ __forceinline__ void ldsm2t(uint32_t addr, uint32_t& a, uint32_t& b) {
  asm volatile("ldmatrix.sync.aligned.m8n8.x2.trans.shared.b16 {%0, %1}, [%2];" : "=r"(a), "=r"(b) : "r"(addr) : "memory");
}
__device__ __forceinline__ void stsm4(uint32_t addr, uint32_t a, uint32_t b, uint32_t c, uint32_t d) {
  asm volatile("stmatrix.sync.aligned.m8n8.x4.shared.b16 [%0], {%1, %2, %3, %4};"
               ::"r"(addr), "r"(a), "r"(b), "r"(c), "r"(d) : "memory");
}
__device__ __forceinline__ void lds128(uint32_t addr, uint32_t& a, uint32_t& b, uint32_t& c, uint32_t& d) {
  asm volatile("ld.shared.v4.b32 {%0, %1, %2, %3}, [%4];" : "=r"(a), "=r"(b), "=r"(c), "=r"(d) : "r"(addr) : "memory");
}
__device__ __forceinline__ void sts128(uint32_t addr, uint32_t a, uint32_t b, uint32_t c, uint32_t d) {
  asm volatile("st.shared.v4.b32 [%0], {%1, %2, %3, %4};" ::"r"(addr), "r"(a), "r"(b), "r"(c), "r"(d) : "memory");
}
__device__ __forceinline__ float2 lds64f(uint32_t addr) {
  float2 v;
  asm volatile("ld.shared.v2.f32 {%0, %1}, [%2];" : "=f"(v.x), "=f"(v.y) : "r"(addr) : "memory");
  return v;
}
__device__ __forceinline__ float lds32f(uint32_t addr) {
  float v;
  asm volatile("ld.shared.f32 %0, [%1];" : "=f"(v) : "r"(addr) : "memory");
  return v;
}
__device__ __forceinline__ uint32_t pack_bf16(float lo, float hi) {
  uint32_t r;
  asm("cvt.rn.bf16x2.f32 %0, %1, %2;" : "=r"(r) : "f"(hi), "f"(lo));
  return r;
}
__device__ __forceinline__ uint32_t pack_bf16_relu(float lo, float hi) {
  uint32_t r;
  asm("cvt.rn.relu.bf16x2.f32 %0, %1, %2;" : "=r"(r) : "f"(hi), "f"(lo));
  return r;
}
__device__ __forceinline__ float ex2(float x) { float y; asm("ex2.approx.ftz.f32 %0, %1;" : "=f"(y) : "f"(x)); return y; }
__device__ __forceinline__ float bf_lo(uint32_t v) { return __uint_as_float(v << 16); }
__device__ __forceinline__ float bf_hi(uint32_t v) { return __uint_as_float(v & 0xffff0000u); }
__device__ __forceinline__ uint32_t lds32(uint32_t addr) {
  uint32_t v;
  asm volatile("ld.shared.b32 %0, [%1];" : "=r"(v) : "r"(addr) : "memory");
  return v;
}
__device__ __forceinline__ void stg_relaxed(uint4* p, uint32_t a, uint32_t b, uint32_t c, uint32_t d) {
  asm volatile("st.relaxed.gpu.global.v4.u32 [%0], {%1, %2, %3, %4};" ::"l"(p), "r"(a), "r"(b), "r"(c), "r"(d) : "memory");
}
template <int STRIDE>
__device__ __forceinline__ void ldg4_relaxed(uint32_t (&w)[16], const uint4* p) {
#pragma unroll
  for (int v = 0; v < 4; v++)
    asm volatile("ld.relaxed.gpu.global.v4.u32 {%0, %1, %2, %3}, [%4];" : "=r"(w[4 * v]), "=r"(w[4 * v + 1]), "=r"(w[4 * v + 2]), "=r"(w[4 * v + 3]) : "l"(p + v * STRIDE) : "memory");
}
template <int STRIDE, uint32_t MASK>
__device__ __forceinline__ void ensure_tagged(uint32_t (&w)[16], const uint4* p, uint32_t tag) {
  asm volatile("{\n.reg .pred p;\n.reg .u32 t;\n"
               "TG_LOOP:\n"
               "xor.b32 t, %0, %17;\n"
               "lop3.b32 t, t, %1, %17, 0xf6;\n"
               "lop3.b32 t, t, %2, %17, 0xf6;\n"
               "lop3.b32 t, t, %3, %17, 0xf6;\n"
               "lop3.b32 t, t, %4, %17, 0xf6;\n"
               "lop3.b32 t, t, %5, %17, 0xf6;\n"
               "lop3.b32 t, t, %6, %17, 0xf6;\n"
               "lop3.b32 t, t, %7, %17, 0xf6;\n"
               "lop3.b32 t, t, %8, %17, 0xf6;\n"
               "lop3.b32 t, t, %9, %17, 0xf6;\n"
               "lop3.b32 t, t, %10, %17, 0xf6;\n"
               "lop3.b32 t, t, %11, %17, 0xf6;\n"
               "lop3.b32 t, t, %12, %17, 0xf6;\n"
               "lop3.b32 t, t, %13, %17, 0xf6;\n"
               "lop3.b32 t, t, %14, %17, 0xf6;\n"
               "lop3.b32 t, t, %15, %17, 0xf6;\n"
               "and.b32 t, t, %18;\nsetp.eq.u32 p, t, 0;\nvote.sync.all.pred p, p, 0xffffffff;\n@p bra.uni TG_DONE;\n"
               "ld.relaxed.gpu.global.v4.u32 {%0, %1, %2, %3}, [%16];\n"
               "ld.relaxed.gpu.global.v4.u32 {%4, %5, %6, %7}, [%16 + %19];\n"
               "ld.relaxed.gpu.global.v4.u32 {%8, %9, %10, %11}, [%16 + %20];\n"
               "ld.relaxed.gpu.global.v4.u32 {%12, %13, %14, %15}, [%16 + %21];\n"
               "bra.uni TG_LOOP;\nTG_DONE:\n}\n"
               : "+r"(w[0]), "+r"(w[1]), "+r"(w[2]), "+r"(w[3]), "+r"(w[4]), "+r"(w[5]), "+r"(w[6]), "+r"(w[7]),
                 "+r"(w[8]), "+r"(w[9]), "+r"(w[10]), "+r"(w[11]), "+r"(w[12]), "+r"(w[13]), "+r"(w[14]), "+r"(w[15])
               : "l"(p), "r"(tag), "n"(MASK), "n"(STRIDE * 16), "n"(STRIDE * 32), "n"(STRIDE * 48) : "memory");
}
__device__ __forceinline__ uint4 ldg_cg(const uint4* p) {
  uint4 v;
  asm volatile("ld.global.cg.v4.u32 {%0, %1, %2, %3}, [%4];" : "=r"(v.x), "=r"(v.y), "=r"(v.z), "=r"(v.w) : "l"(p) : "memory");
  return v;
}
__device__ __forceinline__ uint4 ldg_nc(const void* p) {
  uint4 v;
  asm volatile("ld.global.nc.v4.u32 {%0, %1, %2, %3}, [%4];" : "=r"(v.x), "=r"(v.y), "=r"(v.z), "=r"(v.w) : "l"(p));
  return v;
}
__device__ __forceinline__ void bar_sync(int id, int n) { asm volatile("bar.sync %0, %1;" ::"r"(id), "r"(n) : "memory"); }
__device__ __forceinline__ void wg_fence() { asm volatile("wgmma.fence.sync.aligned;" ::: "memory"); }
__device__ __forceinline__ void wg_commit() { asm volatile("wgmma.commit_group.sync.aligned;" ::: "memory"); }
template <int N> __device__ __forceinline__ void wg_wait() { asm volatile("wgmma.wait_group.sync.aligned %0;" ::"n"(N) : "memory"); }
__device__ __forceinline__ void fence_acc(float (&d)[32]) {
#pragma unroll
  for (int i = 0; i < 32; i++) asm volatile("" : "+f"(d[i])::"memory");
}
__device__ __forceinline__ void fence_acc48(float (&d)[32]) {
#pragma unroll
  for (int i = 0; i < 24; i++) asm volatile("" : "+f"(d[i])::"memory");
}
__device__ __forceinline__ void set_lo(float& d, uint32_t w) { asm volatile("shl.b32 %0, %1, 16;" : "+f"(d) : "r"(w)); }
template <uint32_t MASK>
__device__ __forceinline__ void set_hi(float& d, uint32_t w) { asm volatile("and.b32 %0, %1, %2;" : "+f"(d) : "r"(w), "n"(MASK)); }
__device__ __forceinline__ void acc_add(float& d, float v) { asm volatile("add.f32 %0, %0, %1;" : "+f"(d) : "f"(v)); }
constexpr uint64_t DESC_CONST = ((uint64_t)(8192 >> 4) << 16) | ((uint64_t)(1024 >> 4) << 32) | ((uint64_t)1 << 62);
__device__ __forceinline__ void mma16816(float (&c)[4], uint32_t a0, uint32_t a1, uint32_t a2, uint32_t a3, uint32_t b0, uint32_t b1) {
  asm volatile("mma.sync.aligned.m16n8k16.row.col.f32.bf16.bf16.f32 {%0, %1, %2, %3}, {%4, %5, %6, %7}, {%8, %9}, {%0, %1, %2, %3};"
               : "+f"(c[0]), "+f"(c[1]), "+f"(c[2]), "+f"(c[3]) : "r"(a0), "r"(a1), "r"(a2), "r"(a3), "r"(b0), "r"(b1));
}
__device__ __forceinline__ void mma1688(float (&c)[4], uint32_t a0, uint32_t a1, uint32_t b0) {
  asm volatile("mma.sync.aligned.m16n8k8.row.col.f32.bf16.bf16.f32 {%0, %1, %2, %3}, {%4, %5}, {%6}, {%0, %1, %2, %3};"
               : "+f"(c[0]), "+f"(c[1]), "+f"(c[2]), "+f"(c[3]) : "r"(a0), "r"(a1), "r"(b0));
}

template <int SCALE_D>
__device__ __forceinline__ void wgmma_rs_n64(float (&d)[32], uint32_t a0, uint32_t a1, uint32_t a2, uint32_t a3, uint64_t desc) {
  asm volatile("{\n.reg .pred p;\nsetp.ne.b32 p, %37, 0;\n"
    "wgmma.mma_async.sync.aligned.m64n64k16.f32.bf16.bf16 "
    "{%0, %1, %2, %3, %4, %5, %6, %7, %8, %9, %10, %11, %12, %13, %14, %15, %16, %17, %18, %19, %20, %21, %22, %23, %24, %25, %26, %27, %28, %29, %30, %31}, "
    "{%32,%33,%34,%35}, %36, p, 1, 1, 1;\n}\n"
    : "+f"(d[0]), "+f"(d[1]), "+f"(d[2]), "+f"(d[3]), "+f"(d[4]), "+f"(d[5]), "+f"(d[6]), "+f"(d[7]), "+f"(d[8]), "+f"(d[9]), "+f"(d[10]), "+f"(d[11]), "+f"(d[12]), "+f"(d[13]), "+f"(d[14]), "+f"(d[15]), "+f"(d[16]), "+f"(d[17]), "+f"(d[18]), "+f"(d[19]), "+f"(d[20]), "+f"(d[21]), "+f"(d[22]), "+f"(d[23]), "+f"(d[24]), "+f"(d[25]), "+f"(d[26]), "+f"(d[27]), "+f"(d[28]), "+f"(d[29]), "+f"(d[30]), "+f"(d[31])
    : "r"(a0), "r"(a1), "r"(a2), "r"(a3), "l"(desc), "n"(SCALE_D));
}
__device__ __forceinline__ void wgmma_rs_n64_first(float (&d)[32], uint32_t a0, uint32_t a1, uint32_t a2, uint32_t a3, uint64_t desc) {
  asm volatile("{\n.reg .pred p;\nsetp.ne.b32 p, 0, 0;\n"
    "wgmma.mma_async.sync.aligned.m64n64k16.f32.bf16.bf16 "
    "{%0, %1, %2, %3, %4, %5, %6, %7, %8, %9, %10, %11, %12, %13, %14, %15, %16, %17, %18, %19, %20, %21, %22, %23, %24, %25, %26, %27, %28, %29, %30, %31}, "
    "{%32,%33,%34,%35}, %36, p, 1, 1, 1;\n}\n"
    : "=f"(d[0]), "=f"(d[1]), "=f"(d[2]), "=f"(d[3]), "=f"(d[4]), "=f"(d[5]), "=f"(d[6]), "=f"(d[7]), "=f"(d[8]), "=f"(d[9]), "=f"(d[10]), "=f"(d[11]), "=f"(d[12]), "=f"(d[13]), "=f"(d[14]), "=f"(d[15]), "=f"(d[16]), "=f"(d[17]), "=f"(d[18]), "=f"(d[19]), "=f"(d[20]), "=f"(d[21]), "=f"(d[22]), "=f"(d[23]), "=f"(d[24]), "=f"(d[25]), "=f"(d[26]), "=f"(d[27]), "=f"(d[28]), "=f"(d[29]), "=f"(d[30]), "=f"(d[31])
    : "r"(a0), "r"(a1), "r"(a2), "r"(a3), "l"(desc));
}
template <int SCALE_D>
__device__ __forceinline__ void wgmma_rs_n48(float (&d)[32], uint32_t a0, uint32_t a1, uint32_t a2, uint32_t a3, uint64_t desc) {
  asm volatile("{\n.reg .pred p;\nsetp.ne.b32 p, %29, 0;\n"
    "wgmma.mma_async.sync.aligned.m64n48k16.f32.bf16.bf16 "
    "{%0, %1, %2, %3, %4, %5, %6, %7, %8, %9, %10, %11, %12, %13, %14, %15, %16, %17, %18, %19, %20, %21, %22, %23}, "
    "{%24,%25,%26,%27}, %28, p, 1, 1, 1;\n}\n"
    : "+f"(d[0]), "+f"(d[1]), "+f"(d[2]), "+f"(d[3]), "+f"(d[4]), "+f"(d[5]), "+f"(d[6]), "+f"(d[7]), "+f"(d[8]), "+f"(d[9]), "+f"(d[10]), "+f"(d[11]), "+f"(d[12]), "+f"(d[13]), "+f"(d[14]), "+f"(d[15]), "+f"(d[16]), "+f"(d[17]), "+f"(d[18]), "+f"(d[19]), "+f"(d[20]), "+f"(d[21]), "+f"(d[22]), "+f"(d[23])
    : "r"(a0), "r"(a1), "r"(a2), "r"(a3), "l"(desc), "n"(SCALE_D));
}
__device__ __forceinline__ void wgmma_rs_n48_first(float (&d)[32], uint32_t a0, uint32_t a1, uint32_t a2, uint32_t a3, uint64_t desc) {
  asm volatile("{\n.reg .pred p;\nsetp.ne.b32 p, 0, 0;\n"
    "wgmma.mma_async.sync.aligned.m64n48k16.f32.bf16.bf16 "
    "{%0, %1, %2, %3, %4, %5, %6, %7, %8, %9, %10, %11, %12, %13, %14, %15, %16, %17, %18, %19, %20, %21, %22, %23}, "
    "{%24,%25,%26,%27}, %28, p, 1, 1, 1;\n}\n"
    : "=f"(d[0]), "=f"(d[1]), "=f"(d[2]), "=f"(d[3]), "=f"(d[4]), "=f"(d[5]), "=f"(d[6]), "=f"(d[7]), "=f"(d[8]), "=f"(d[9]), "=f"(d[10]), "=f"(d[11]), "=f"(d[12]), "=f"(d[13]), "=f"(d[14]), "=f"(d[15]), "=f"(d[16]), "=f"(d[17]), "=f"(d[18]), "=f"(d[19]), "=f"(d[20]), "=f"(d[21]), "=f"(d[22]), "=f"(d[23])
    : "r"(a0), "r"(a1), "r"(a2), "r"(a3), "l"(desc));
}

#define TSTAMP(idx) do {} while (0)
#define GSTAMP(idx) do {} while (0)
#define WSTAMP(idx) do {} while (0)
#define RSTAMP(idx) do {} while (0)

struct Params {
  const __nv_bfloat16* x;
  __nv_bfloat16* out;
  uint64_t desc_const;
};

template <int n, int AOFF, int NKS, int FIRST, bool N48>
__device__ __forceinline__ void issue_tile(float (&acc)[32], const uint32_t (&A)[128], uint32_t sb, uint64_t ring_desc) {
  constexpr int m = n / 2;
  if constexpr ((n & 1) == 0) {
    if (threadIdx.x < 32) RSTAMP(40 + m);
    mbar_spin(sb + OFF_BAR + (B_FULL + m) * 8, 0);
    if (threadIdx.x < 32) RSTAMP(80 + m);
  }
  wg_fence();
  uint64_t tile_desc = ring_desc;
  asm volatile("" : "+l"(tile_desc));
  auto step = [&](auto KS) {
    constexpr int ks = decltype(KS)::value;
    if constexpr (ks < NKS) {
      const uint64_t d = tile_desc + ((ds_buf(m) * 16384 + (n & 1) * 8192 + ks * 2048) >> 4);
      constexpr int first = ks == 0 ? FIRST : 0;
      const uint32_t a0 = A[AOFF + 4 * ks], a1 = A[AOFF + 4 * ks + 1], a2 = A[AOFF + 4 * ks + 2], a3 = A[AOFF + 4 * ks + 3];
      if constexpr (N48 && first == 2) wgmma_rs_n48_first(acc, a0, a1, a2, a3, d);
      else if constexpr (N48) wgmma_rs_n48<first ? 0 : 1>(acc, a0, a1, a2, a3, d);
      else if constexpr (first == 2) wgmma_rs_n64_first(acc, a0, a1, a2, a3, d);
      else wgmma_rs_n64<first ? 0 : 1>(acc, a0, a1, a2, a3, d);
    }
  };
  step(std::integral_constant<int, 0>{}); step(std::integral_constant<int, 1>{});
  step(std::integral_constant<int, 2>{}); step(std::integral_constant<int, 3>{});
  wg_commit();
}
template <int t>
__device__ __forceinline__ void release_tile(uint32_t sb, int lane) {
  if constexpr (t >= 0 && (t & 1) == 1) {
    if constexpr (ds_release_needed(t / 2)) {
      if (lane == 0) mbar_arrive(sb + OFF_BAR + (B_EMPTY + t / 2) * 8);
    }
  }
}
template <int n, int L>
__device__ __forceinline__ void retire(uint32_t sb, int lane) {
  wg_wait<L>();
  release_tile<n - L>(sb, lane);
}

struct RowStats { float mean0, mean1, r0, r1; };

template <bool RELU>
__device__ __forceinline__ void epi16(const float (&acc)[32], int g, uint32_t cs_addr, const RowStats& st, float r0, float r1,
                                      uint32_t& p0, uint32_t& p1, uint32_t& p2, uint32_t& p3) {
  const float2 c0 = lds64f(cs_addr + (16 * g) * 4);
  const float2 c1 = lds64f(cs_addr + (16 * g + 8) * 4);
  const float y0 = fmaf(-st.mean0, c0.x, acc[8 * g + 0]) * r0, y1 = fmaf(-st.mean0, c0.y, acc[8 * g + 1]) * r0;
  const float y2 = fmaf(-st.mean1, c0.x, acc[8 * g + 2]) * r1, y3 = fmaf(-st.mean1, c0.y, acc[8 * g + 3]) * r1;
  const float y4 = fmaf(-st.mean0, c1.x, acc[8 * g + 4]) * r0, y5 = fmaf(-st.mean0, c1.y, acc[8 * g + 5]) * r0;
  const float y6 = fmaf(-st.mean1, c1.x, acc[8 * g + 6]) * r1, y7 = fmaf(-st.mean1, c1.y, acc[8 * g + 7]) * r1;
  if (RELU) { p0 = pack_bf16_relu(y0, y1); p1 = pack_bf16_relu(y2, y3); p2 = pack_bf16_relu(y4, y5); p3 = pack_bf16_relu(y6, y7); }
  else { p0 = pack_bf16(y0, y1); p1 = pack_bf16(y2, y3); p2 = pack_bf16(y4, y5); p3 = pack_bf16(y6, y7); }
}

template <bool RELU>
__device__ __forceinline__ void epi16s(const float (&acc)[32], int g, float r0, float r1, uint32_t& p0, uint32_t& p1, uint32_t& p2, uint32_t& p3) {
  const float y0 = acc[8 * g + 0] * r0, y1 = acc[8 * g + 1] * r0, y2 = acc[8 * g + 2] * r1, y3 = acc[8 * g + 3] * r1;
  const float y4 = acc[8 * g + 4] * r0, y5 = acc[8 * g + 5] * r0, y6 = acc[8 * g + 6] * r1, y7 = acc[8 * g + 7] * r1;
  if (RELU) { p0 = pack_bf16_relu(y0, y1); p1 = pack_bf16_relu(y2, y3); p2 = pack_bf16_relu(y4, y5); p3 = pack_bf16_relu(y6, y7); }
  else { p0 = pack_bf16(y0, y1); p1 = pack_bf16(y2, y3); p2 = pack_bf16(y4, y5); p3 = pack_bf16(y6, y7); }
}
__device__ __forceinline__ uint32_t sub_bf16x2(uint32_t a, uint32_t b) {
  uint32_t r;
  asm("sub.rn.bf16x2 %0, %1, %2;" : "=r"(r) : "r"(a), "r"(b));
  return r;
}

template <int OFFSET>
__device__ __forceinline__ uint32_t frag_addr(uint32_t frag0, int g) {
  uint32_t r;
  asm volatile("xor.b32 %0, %1, %2;" : "=r"(r) : "r"(frag0), "r"(g << 5));
  return r + OFFSET;
}

#define IC(v) std::integral_constant<int, (v)>{}
template <int I, int E, class F>
__device__ __forceinline__ void static_for(F&& f) {
  if constexpr (I < E) { f(std::integral_constant<int, I>{}); static_for<I + 1, E>(f); }
}

__global__ void __cluster_dims__(2, 1, 1) __launch_bounds__(384, 1)
fused_kernel(const __grid_constant__ CUtensorMap tmX, const __grid_constant__ CUtensorMap tmWqkv,
             const __grid_constant__ CUtensorMap tmW1, const __grid_constant__ CUtensorMap tmWo,
             const __grid_constant__ CUtensorMap tmW2, Params prm) {
  extern __shared__ uint8_t smem_raw[];
  const uint32_t sb = (smem_u32(smem_raw) + 1023u) & ~1023u;
  const int warp = __shfl_sync(0xffffffffu, threadIdx.x >> 5, 0);
  const int lane = threadIdx.x & 31;
  const int ti = blockIdx.x >> 3;
  const int tj = blockIdx.x & 7;
  const int ta = tj >> 1, tb = tj & 1;

  if (warp >= 8) {
    uint32_t nload = 0;
    auto load_pair = [&](const CUtensorMap* m0, int c0, int r0, const CUtensorMap* m1, int c1, int r1) {
      const uint32_t w = nload >> 2;
      const uint64_t word = w == 0 ? ds_word(0) : w == 1 ? ds_word(1) : w == 2 ? ds_word(2) : w == 3 ? ds_word(3) : w == 4 ? ds_word(4)
                          : w == 5 ? ds_word(5) : w == 6 ? ds_word(6) : w == 7 ? ds_word(7) : w == 8 ? ds_word(8) : ds_word(9);
      const uint32_t e = (uint32_t)(word >> (16 * (nload & 3))), wb = (e >> 4) & 0xff;
      if (wb != 0xff) mbar_wait(sb + OFF_BAR + wb * 8, 0);
      if (elect_one()) {
        const uint32_t bar = sb + OFF_BAR + (B_FULL + nload) * 8, dst = sb + (e & 15) * 16384;
        mbar_expect_tx(bar, 16384);
        tma_load(dst, m0, bar, c0, r0);
        tma_load(dst + 8192, m1, bar, c1, r1);
      }
      __syncwarp();
      RSTAMP(nload);
      nload++;
    };
    auto load_x_w = [&](int kb) {
      if (elect_one()) {
        tma_load(sb + OFF_U + kb * 16384, &tmX, sb + OFF_BAR + (B_X + 2 * kb) * 8, 64 * kb, 64 * ti);
        tma_load(sb + OFF_U + kb * 16384 + 8192, &tmX, sb + OFF_BAR + (B_X + 2 * kb + 1) * 8, 512 + 64 * kb, 64 * ti);
      }
      __syncwarp();
      load_pair(&tmWqkv, 64 * tj, 64 * kb, &tmWqkv, 512 + 64 * tj, 64 * kb);
    };
    const int hw = warp - 9;
    uint32_t epoch = 0;
    if (warp == 8) {
      TSTAMP(59); GSTAMP(60);
      if (elect_one()) {
        const uint32_t bb = sb + OFF_BAR;
        prefetch_tmap(&tmX); prefetch_tmap(&tmWqkv);
#pragma unroll
        for (int t = 0; t < 2; t++) mbar_init(bb + (B_FULL + t) * 8, 1);
#pragma unroll
        for (int t = 0; t < 4; t++) { mbar_init(bb + (B_X + t) * 8, 1); mbar_expect_tx(bb + (B_X + t) * 8, 8192); }
        asm volatile("fence.mbarrier_init.release.cluster;" ::: "memory");
      }
      __syncwarp();
      TSTAMP(0);
      load_x_w(0); load_x_w(1);
      if (elect_one()) {
        tma_prefetch(&tmX, 512 * (tj & 1) + 64 * (tj >> 1), 64 * ti);
        tma_prefetch(&tmX, 512 * (tj & 1) + 64 * (4 + (tj >> 1)), 64 * ti);
        tma_prefetch(&tmWqkv, 512 * (ti & 1) + 64 * tj, 64 * (ti >> 1));
      }
      __syncwarp();
      TSTAMP(36);
      bar_sync(0, 384);
      asm volatile("barrier.cluster.arrive.relaxed.aligned;" ::: "memory");
    } else {
      asm volatile("ld.global.u32 %0, [%1];" : "=r"(epoch) : "l"(&g_launch_cnt[blockIdx.x]) : "memory");
      if (hw == 2) { asm volatile("st.shared.v4.b32 [%0], {%1, %1, %1, %1};" ::"r"(sb + OFF_CS + lane * 16), "r"(0u) : "memory"); }
      if (elect_one()) {
        const uint32_t bb = sb + OFF_BAR;
        if (hw == 0) {
#pragma unroll
          for (int t = 0; t < 10; t++) mbar_init(bb + (B_LAND + t) * 8, 1);
#pragma unroll
          for (int t = 0; t < 10; t++) mbar_expect_tx(bb + (B_LAND + t) * 8, (t == 6 || t == 7) ? 6144 : 8192);
#pragma unroll
          for (int t = 4; t < 16; t++) { mbar_init(bb + (B_X + t) * 8, 1); mbar_expect_tx(bb + (B_X + t) * 8, 8192); }
        } else if (hw == 1) {
          mbar_init(bb + B_QKV * 8, 8); mbar_init(bb + B_O * 8, 8); mbar_init(bb + B_CS * 8, 3); mbar_init(bb + B_PEERX * 8, 8);
          mbar_init(bb + B_PEERX2 * 8, 8); mbar_init(bb + B_HALO * 8, 3); mbar_init(bb + B_DONE * 8, 8);
          mbar_init(bb + B_LAG * 8, 4); mbar_init(bb + (B_LAG + 1) * 8, 4);
          mbar_init(bb + B_XC * 8, 8); mbar_init(bb + B_U03 * 8, 8); mbar_init(bb + B_LF * 8, 8);
#pragma unroll
          for (int t = 2; t < 20; t++) mbar_init(bb + (B_FULL + t) * 8, 1);
        } else {
          prefetch_tmap(&tmW1); prefetch_tmap(&tmWo); prefetch_tmap(&tmW2);
#pragma unroll
          for (int t = 20; t < NDS; t++) mbar_init(bb + (B_FULL + t) * 8, 1);
        }
        asm volatile("fence.mbarrier_init.release.cluster;" ::: "memory");
      }
      bar_sync(0, 384);
      asm volatile("barrier.cluster.arrive.relaxed.aligned;" ::: "memory");
    }
    asm volatile("setmaxnreg.dec.sync.aligned.u32 56;");
    if (warp == 8) {
#pragma unroll 1
      for (int kb = 2; kb < 8; kb++) {
        mbar_wait(sb + OFF_BAR + (B_FULL + kb - 2) * 8, 0);
        load_x_w(kb);

        if (kb == 4) {
          if (elect_one()) {
#pragma unroll 1
            for (int m = 2 * ti; m < 2 * ti + 2; m++) {
              if (m < 8) tma_prefetch(&tmWqkv, 1024 + 64 * tj, 64 * m);
              else tma_prefetch(&tmW1, kFS * tj + 64 * ((m - 8) >> 3), 64 * ((m - 8) & 7));
              const int t = m & 7, c0 = 256 * tb + 64 * (m >> 3);
              const int jj = (t == 1 || t == 4 || t == 5 || t == 7) ? (tj ^ 1) : tj;
              if (t < 2) tma_prefetch(&tmWo, c0, 64 * jj);
              else tma_prefetch(&tmW2, c0, kFS * jj + (t >= 6 ? 128 : ((t == 3 || t == 5) ? 64 : 0)));
            }
          }
          __syncwarp();
        }
      }
#pragma unroll 1
      for (int it = 0; it < 16; it++) {
        const int job = it >> 2, r = 128 * (it & 3);
        const CUtensorMap* tm = job == 0 ? &tmWqkv : &tmW1;
        const int c0 = job == 0 ? 1024 + 64 * tj : kFS * tj + 64 * (job - 1);
        load_pair(tm, c0, r, tm, c0, r + 64);
      }
#pragma unroll 1
      for (int blk = 0; blk < 4; blk++) {
        const int c0 = 256 * tb + 64 * ((ta + 1 + blk) & 3);
        const int ro = kFS * tj, rp = kFS * (tj ^ 1);
        load_pair(&tmWo, c0, 64 * tj, &tmWo, c0, 64 * (tj ^ 1));
        load_pair(&tmW2, c0, ro, &tmW2, c0, ro + 64);
        load_pair(&tmW2, c0, rp, &tmW2, c0, rp + 64);
        load_pair(&tmW2, c0, ro + 128, &tmW2, c0, rp + 128);
        if (blk == 2) {
          if (elect_one()) {
            asm volatile("fence.proxy.async.shared::cta;" ::: "memory");
            tma_load(sb + OFF_U + 7 * 16384, &tmX, sb + OFF_BAR + B_RES * 8, 256 * tb + 64 * ta, 64 * ti);
            tma_load(sb + OFF_U + 7 * 16384 + 8192, &tmX, sb + OFF_BAR + (B_RES + 1) * 8, 512 + 256 * tb + 64 * ta, 64 * ti);
          }
          __syncwarp();
        }
      }
      TSTAMP(1);
      mbar_wait(sb + OFF_BAR + B_DONE * 8, 0);
    } else {
      epoch += 1;
      if (hw == 2 && lane == 0) asm volatile("st.shared.b32 [%0], %1;" ::"r"(sb + OFF_TAG), "r"(epoch & 3u) : "memory");
      {
        const int rs = lane >> 3;
        const uint8_t* gbase;
        asm volatile("cvta.shared.u64 %0, %1;" : "=l"(gbase) : "l"((uint64_t)(sb + R0 * 16384)));
        float sa[8], sc[8];
#pragma unroll
        for (int k = 0; k < 8; k++) { sa[k] = 0.f; sc[k] = 0.f; }
#pragma unroll 1
        for (int m = 0; m < NDS0; m++) {
          mbar_wait(sb + OFF_BAR + (B_FULL + m) * 8, 0);
          if (hw == 0 && m < 2) TSTAMP(52 + m);
          const uint8_t* src = gbase + m * 16384;
          asm volatile("" : "+l"(src) :: "memory");
#pragma unroll
          for (int i = 0; i < 6; i++) {
            const int quad = hw + 3 * i;
            if (i < 5 || hw == 0) {
              const int row = 4 * quad + rs;
              const uint8_t* a = src + row * 128 + (((lane & 7) ^ (row & 7)) << 4);
              uint32_t w0, w1, w2, w3, v0, v1, v2, v3;
              asm("ld.v4.b32 {%0, %1, %2, %3}, [%4];" : "=r"(w0), "=r"(w1), "=r"(w2), "=r"(w3) : "l"(a));
              asm("ld.v4.b32 {%0, %1, %2, %3}, [%4];" : "=r"(v0), "=r"(v1), "=r"(v2), "=r"(v3) : "l"(a + 8192));
              sa[0] += bf_lo(w0); sa[1] += bf_hi(w0); sa[2] += bf_lo(w1); sa[3] += bf_hi(w1);
              sa[4] += bf_lo(w2); sa[5] += bf_hi(w2); sa[6] += bf_lo(w3); sa[7] += bf_hi(w3);
              sc[0] += bf_lo(v0); sc[1] += bf_hi(v0); sc[2] += bf_lo(v1); sc[3] += bf_hi(v1);
              sc[4] += bf_lo(v2); sc[5] += bf_hi(v2); sc[6] += bf_lo(v3); sc[7] += bf_hi(v3);
            }
          }
          asm volatile("" : "+f"(sa[0]), "+f"(sa[1]), "+f"(sa[2]), "+f"(sa[3]), "+f"(sa[4]), "+f"(sa[5]), "+f"(sa[6]), "+f"(sa[7]),
                            "+f"(sc[0]), "+f"(sc[1]), "+f"(sc[2]), "+f"(sc[3]), "+f"(sc[4]), "+f"(sc[5]), "+f"(sc[6]), "+f"(sc[7]) :: "memory");
          __syncwarp();
          if (lane == 0) mbar_arrive(sb + OFF_BAR + (B_EMPTY + m) * 8);
        }
        const bool b4 = lane & 16, b3 = lane & 8;
        auto reduce = [&](float (&v)[8], uint32_t dst) {
#pragma unroll
          for (int k = 0; k < 4; k++) { const float snd = b4 ? v[k] : v[k + 4], keep = b4 ? v[k + 4] : v[k]; v[k] = keep + __shfl_xor_sync(0xffffffffu, snd, 16); }
#pragma unroll
          for (int k = 0; k < 2; k++) { const float snd = b3 ? v[k] : v[k + 2], keep = b3 ? v[k + 2] : v[k]; v[k] = keep + __shfl_xor_sync(0xffffffffu, snd, 8); }
          asm volatile("red.shared.add.f32 [%0], %1;" ::"r"(dst), "f"(v[0]) : "memory");
          asm volatile("red.shared.add.f32 [%0], %1;" ::"r"(dst + 4), "f"(v[1]) : "memory");
        };
        const uint32_t dst = sb + OFF_CS + (8 * (lane & 7) + (b4 ? 4 : 0) + (b3 ? 2 : 0)) * 4;
        reduce(sa, dst); reduce(sc, dst + 256);
        __syncwarp();
        if (lane == 0) mbar_arrive(sb + OFF_BAR + B_CS * 8);
        if (hw < 2) TSTAMP(2 + hw);
      }
      if (hw == 2 && lane == 0) g_launch_cnt[blockIdx.x] = epoch;
      {
        const uint32_t tag = epoch & 3u;
        mbar_wait(sb + OFF_BAR + B_QKV * 8, 0);
#pragma unroll 1
        for (int u = hw; u < 4; u += 3) {
          uint32_t w[16];
          if (ti > 0) {
            const uint4* src = &g_halo[((ti - 1) * 8 + tj) * 512 + u * 128 + lane];
            ldg4_relaxed<32>(w, src);
            ensure_tagged<32, 3u>(w, src, tag);
          } else {
#pragma unroll
            for (int e = 0; e < 16; e++) w[e] = 0u;
          }
          const uint32_t dst = sb + OFF_HALO + u * 1024 + (lane >> 2) * 128 + (lane & 3) * 4;
#pragma unroll
          for (int v = 0; v < 4; v++) {
            const uint32_t lo = __byte_perm(w[4 * v], w[4 * v + 1], 0x7632), hi = __byte_perm(w[4 * v + 2], w[4 * v + 3], 0x7632);
            asm volatile("st.shared.b32 [%0], %1;" ::"r"(dst + (((2 * v) ^ (lane >> 2)) << 4)), "r"(lo) : "memory");
            asm volatile("st.shared.b32 [%0], %1;" ::"r"(dst + (((2 * v + 1) ^ (lane >> 2)) << 4)), "r"(hi) : "memory");
          }
        }
        __syncwarp();
        if (lane == 0) mbar_arrive(sb + OFF_BAR + B_HALO * 8);
        if (hw == 2) TSTAMP(31);
      }
    }
  } else {
    const int p = warp >> 2;
    const int wq = warp & 3;
    const int tw = threadIdx.x & 127;
    const int q = lane & 3;
    uint32_t A[128];
    float acc0[32], acc1[32];
    const uint32_t frag0 = sb + OFF_U + p * 8192 + wq * 2048 + (lane & 15) * 128 + (((lane >> 4) ^ (lane & 7)) << 4);
    const uint32_t peer_sb = mapa(sb, tb ^ 1);
    const uint64_t ring_desc = prm.desc_const + ((sb & 0x3FFFF) >> 4);

    uint32_t tag;
    {
      const int r = 8 * tj + 2 * wq;
      uint32_t epoch;
      asm volatile("ld.global.u32 %0, [%1];" : "=r"(epoch) : "l"(&g_launch_cnt[blockIdx.x]) : "memory");
      const uint4* src = reinterpret_cast<const uint4*>(prm.x + (size_t)(2 * (64 * ti + r) + p) * 512) + lane;
      const uint4 u0 = ldg_nc(src), u1 = ldg_nc(src + 32), w0 = ldg_nc(src + 128), w1 = ldg_nc(src + 160);
      if (elect_one()) {
#pragma unroll
        for (int t = 0; t < 5; t++) mbar_init(sb + OFF_BAR + (B_EMPTY + t) * 8 + warp * 40, (warp == 0 && t < NDS0) ? 11 : 8);
        asm volatile("fence.mbarrier_init.release.cluster;" ::: "memory");
      }
      bar_sync(0, 384);
      asm volatile("barrier.cluster.arrive.relaxed.aligned;" ::: "memory");
      tag = (epoch + 1) & 3u;
      const float sh0 = __shfl_sync(0xffffffffu, bf_lo(u0.x), 0), sh1 = __shfl_sync(0xffffffffu, bf_lo(w0.x), 0);
      float s0 = 0.f, q0 = 0.f, s1 = 0.f, q1 = 0.f;
      auto accum = [](uint32_t v, float sh, float& s, float& q) {
        const float a = bf_lo(v) - sh, b = bf_hi(v) - sh;
        s += a + b; q = fmaf(a, a, fmaf(b, b, q));
      };
      accum(u0.x, sh0, s0, q0); accum(u0.y, sh0, s0, q0); accum(u0.z, sh0, s0, q0); accum(u0.w, sh0, s0, q0);
      accum(u1.x, sh0, s0, q0); accum(u1.y, sh0, s0, q0); accum(u1.z, sh0, s0, q0); accum(u1.w, sh0, s0, q0);
      accum(w0.x, sh1, s1, q1); accum(w0.y, sh1, s1, q1); accum(w0.z, sh1, s1, q1); accum(w0.w, sh1, s1, q1);
      accum(w1.x, sh1, s1, q1); accum(w1.y, sh1, s1, q1); accum(w1.z, sh1, s1, q1); accum(w1.w, sh1, s1, q1);
      asm volatile("" : "+f"(s0), "+f"(s1), "+f"(q0), "+f"(q1));
      WSTAMP(57);
      const bool hi = lane & 16;
      float ss = (hi ? s1 : s0) + __shfl_xor_sync(0xffffffffu, hi ? s0 : s1, 16);
      float qq = (hi ? q1 : q0) + __shfl_xor_sync(0xffffffffu, hi ? q0 : q1, 16);
#pragma unroll
      for (int o = 8; o >= 1; o >>= 1) { ss += __shfl_xor_sync(0xffffffffu, ss, o); qq += __shfl_xor_sync(0xffffffffu, qq, o); }
      if ((lane & 15) == 0) {
        const float m = ss * (1.f / 512.f);
        const float var = fmaxf(qq * (1.f / 512.f) - m * m, 0.f);
        const float mean = __bfloat162float(__float2bfloat16_rn((hi ? sh1 : sh0) + m)), rstd = 1.f / sqrtf(var + 1e-5f);
        uint32_t* dst = reinterpret_cast<uint32_t*>(g_st) + (ti * 128 + 64 * p + r + (hi ? 1 : 0)) * 2;
        asm volatile("st.relaxed.gpu.global.v2.u32 [%0], {%1, %2};" ::"l"(dst), "r"((__float_as_uint(mean) & ~3u) | tag), "r"((__float_as_uint(rstd) & ~3u) | tag) : "memory");
      }
    }
    asm volatile("setmaxnreg.inc.sync.aligned.u32 224;");
    auto load_x_block = [&](auto KB) {
      constexpr int kb = decltype(KB)::value;
      mbar_spin(sb + OFF_BAR + (B_X + 2 * kb + p) * 8, 0);
#pragma unroll
      for (int ks = 0; ks < 4; ks++)
        ldsm4(frag_addr<kb * 16384>(frag0, ks), A[16 * kb + 4 * ks], A[16 * kb + 4 * ks + 1], A[16 * kb + 4 * ks + 2], A[16 * kb + 4 * ks + 3]);
    };

    const uint32_t st_addr = sb + OFF_ST + (64 * p + 16 * wq + (lane >> 2)) * 8;
    auto center = [&](auto FROM, auto TO) {
      const float m0 = lds32f(st_addr), m1 = lds32f(st_addr + 64);
      const uint32_t m2a = pack_bf16(m0, m0), m2b = pack_bf16(m1, m1);
#pragma unroll
      for (int i = decltype(FROM)::value; i < decltype(TO)::value; i += 2) { A[i] = sub_bf16x2(A[i], m2a); A[i + 1] = sub_bf16x2(A[i + 1], m2b); }
    };
    WSTAMP(16);
    load_x_block(IC(0));
    uint2 sv0, sv1;
    auto j0_step = [&](auto KB) {
      constexpr int kb = decltype(KB)::value;
      issue_tile<2 * kb, 16 * kb, 4, (kb == 0 ? 2 : 0), false>(acc0, A, sb, ring_desc);
      issue_tile<2 * kb + 1, 16 * kb, 4, (kb == 0 ? 2 : 0), false>(acc1, A, sb, ring_desc);
      if constexpr (kb == 0 || kb == 3) { WSTAMP(48 + kb); }
      if constexpr (kb < 7) load_x_block(IC(kb + 1));
      if constexpr (kb == NDS0 - 2) {
        const uint2* src = reinterpret_cast<const uint2*>(g_st) + ti * 128 + 64 * p + 16 * wq + (lane >> 2);
        asm volatile("ld.relaxed.gpu.global.v2.u32 {%0, %1}, [%2];" : "=r"(sv0.x), "=r"(sv0.y) : "l"(src) : "memory");
        asm volatile("ld.relaxed.gpu.global.v2.u32 {%0, %1}, [%2 + 64];" : "=r"(sv1.x), "=r"(sv1.y) : "l"(src) : "memory");
      }
      if constexpr (kb == NDS0 - 1) {
        const uint2* src = reinterpret_cast<const uint2*>(g_st) + ti * 128 + 64 * p + 16 * wq + (lane >> 2);
        asm volatile("{\n.reg .pred p;\n.reg .u32 t, u;\n"
                     "ST_LOOP:\nxor.b32 t, %0, %5;\nxor.b32 u, %1, %5;\nor.b32 t, t, u;\nxor.b32 u, %2, %5;\nor.b32 t, t, u;\nxor.b32 u, %3, %5;\nor.b32 t, t, u;\n"
                     "and.b32 t, t, 3;\nsetp.eq.u32 p, t, 0;\nvote.sync.all.pred p, p, 0xffffffff;\n@p bra.uni ST_DONE;\n"
                     "ld.relaxed.gpu.global.v2.u32 {%0, %1}, [%4];\nld.relaxed.gpu.global.v2.u32 {%2, %3}, [%4 + 64];\n"
                     "bra.uni ST_LOOP;\nST_DONE:\n}\n"
                     : "+r"(sv0.x), "+r"(sv0.y), "+r"(sv1.x), "+r"(sv1.y) : "l"(src), "r"(tag) : "memory");
        if (q == 0) {
          asm volatile("st.shared.v2.b32 [%0], {%1, %2};" ::"r"(st_addr), "r"(sv0.x), "r"(sv0.y) : "memory");
          asm volatile("st.shared.v2.b32 [%0], {%1, %2};" ::"r"(st_addr + 64), "r"(sv1.x), "r"(sv1.y) : "memory");
        }
        __syncwarp();
        WSTAMP(4);
      }
      if constexpr (kb < 7) { wg_wait<2>(); release_tile<2 * kb - 1>(sb, lane); }
      if constexpr (kb == NDS0 - 1) { center(IC(0), IC(16 * (NDS0 - 1))); center(IC(16 * NDS0), IC(16 * NDS0 + 16)); }
      else if constexpr (kb == NDS0) { center(IC(16 * (NDS0 - 1)), IC(16 * NDS0)); center(IC(16 * (kb + 1)), IC(16 * (kb + 2))); }
      else if constexpr (kb > NDS0 && kb < 7) center(IC(16 * (kb + 1)), IC(16 * (kb + 2)));
    };
    j0_step(IC(0)); j0_step(IC(1)); j0_step(IC(2)); j0_step(IC(3)); j0_step(IC(4)); j0_step(IC(5));
    if (p == 1) mbar_spin(sb + OFF_BAR + B_LAG * 8, 0);
    issue_tile<12, 96, 4, 0, false>(acc0, A, sb, ring_desc);
    load_x_block(IC(7));
    wg_wait<1>(); release_tile<11>(sb, lane);
    center(IC(112), IC(128));
    asm volatile("barrier.cluster.wait.aligned;" ::: "memory");
    if (lane == 0) { mbar_arrive(sb + OFF_BAR + B_XC * 8); mbar_arrive_remote(peer_sb + OFF_BAR + B_PEERX * 8); }
    issue_tile<14, 112, 4, 0, false>(acc0, A, sb, ring_desc);
    issue_tile<13, 96, 4, 0, false>(acc1, A, sb, ring_desc);
    if (p == 0 && lane == 0) mbar_arrive(sb + OFF_BAR + B_LAG * 8);
    issue_tile<15, 112, 4, 0, false>(acc1, A, sb, ring_desc);
    WSTAMP(18);
    const uint32_t cs_lane = sb + OFF_CS + (2 * q) * 4;
    auto export_halo = [&](int kv, int g, uint32_t tg, uint32_t p1, uint32_t p3) {
      uint32_t ll = lane;
      asm volatile("" : "+r"(ll));
      stg_relaxed(&g_halo[(ti * 8 + tj) * 512 + (kv * 2 + p) * 128 + g * 32 + ll], (p1 << 16) | tg, (p1 & 0xffff0000u) | tg, (p3 << 16) | tg, (p3 & 0xffff0000u) | tg);
    };
    const bool exporter = wq == 3 && ti < 15;
    auto epi_qk = [&](const float (&acc)[32], auto UNIT, float scale) {
      constexpr int unit = decltype(UNIT)::value;
      const float2 sa = lds64f(st_addr), sc = lds64f(st_addr + 64);
      float2 c0 = lds64f(cs_lane + unit * 256), c1 = lds64f(cs_lane + unit * 256 + 32);
      const uint32_t tg = unit == 1 ? lds32(sb + OFF_TAG) : 0u;
      const float r0 = sa.y * scale, r1 = sc.y * scale;
#pragma unroll
      for (int g = 0; g < 4; g++) {
        float2 n0 = c0, n1 = c1;
        if (g < 3) { n0 = lds64f(cs_lane + unit * 256 + (g + 1) * 64); n1 = lds64f(cs_lane + unit * 256 + (g + 1) * 64 + 32); }
        const uint32_t p0 = pack_bf16(fmaf(-sa.x, c0.x, acc[8 * g + 0]) * r0, fmaf(-sa.x, c0.y, acc[8 * g + 1]) * r0);
        const uint32_t p1 = pack_bf16(fmaf(-sc.x, c0.x, acc[8 * g + 2]) * r1, fmaf(-sc.x, c0.y, acc[8 * g + 3]) * r1);
        const uint32_t p2 = pack_bf16(fmaf(-sa.x, c1.x, acc[8 * g + 4]) * r0, fmaf(-sa.x, c1.y, acc[8 * g + 5]) * r0);
        const uint32_t p3 = pack_bf16(fmaf(-sc.x, c1.x, acc[8 * g + 6]) * r1, fmaf(-sc.x, c1.y, acc[8 * g + 7]) * r1);
        stsm4(frag_addr<unit * 16384>(frag0, g), p0, p1, p2, p3);
        if (unit == 1 && exporter) export_halo(0, g, tg, p1, p3);
        c0 = n0; c1 = n1;
      }
    };
    wg_wait<2>();
    fence_acc(acc0);
    mbar_spin(sb + OFF_BAR + B_CS * 8, 0);
    WSTAMP(37);
    epi_qk(acc0, IC(0), 0.25f);
    WSTAMP(19);

    issue_tile<16, 0, 4, 1, false>(acc0, A, sb, ring_desc);
    issue_tile<17, 16, 4, 0, false>(acc0, A, sb, ring_desc);
    wg_wait<2>(); release_tile<13>(sb, lane); release_tile<15>(sb, lane);
    issue_tile<18, 32, 4, 0, false>(acc0, A, sb, ring_desc);
    issue_tile<19, 48, 4, 0, false>(acc0, A, sb, ring_desc);
    fence_acc(acc1);
    epi_qk(acc1, IC(1), 1.f);
    wg_wait<2>(); release_tile<17>(sb, lane);
    issue_tile<20, 64, 4, 0, false>(acc0, A, sb, ring_desc); retire<20, LAG>(sb, lane);
    issue_tile<21, 80, 4, 0, false>(acc0, A, sb, ring_desc); retire<21, LAG>(sb, lane);
    issue_tile<22, 96, 4, 0, false>(acc0, A, sb, ring_desc); retire<22, LAG>(sb, lane);
    issue_tile<23, 112, 4, 0, false>(acc0, A, sb, ring_desc); retire<23, LAG>(sb, lane);
    WSTAMP(27);

    const uint32_t rs_addr = st_addr + 4;
    issue_tile<24, 0, 4, 1, false>(acc1, A, sb, ring_desc); retire<24, LAG>(sb, lane);
    issue_tile<25, 16, 4, 0, false>(acc1, A, sb, ring_desc); retire<25, LAG>(sb, lane);
    issue_tile<26, 32, 4, 0, false>(acc1, A, sb, ring_desc);
    issue_tile<27, 48, 4, 0, false>(acc1, A, sb, ring_desc);
    fence_acc(acc0);
    {
      const float r0 = lds32f(rs_addr), r1 = lds32f(rs_addr + 64);
      const uint32_t tg = lds32(sb + OFF_TAG);
#pragma unroll
      for (int g = 0; g < 4; g++) {
        uint32_t p0, p1, p2, p3;
        epi16s<false>(acc0, g, r0, r1, p0, p1, p2, p3);
        stsm4(frag_addr<2 * 16384>(frag0, g), p0, p1, p2, p3);
        if (exporter) export_halo(1, g, tg, p1, p3);
      }
    }
    if (lane == 0) mbar_arrive(sb + OFF_BAR + B_QKV * 8);
    WSTAMP(20);
    wg_wait<2>(); release_tile<25>(sb, lane);
    issue_tile<28, 64, 4, 0, false>(acc1, A, sb, ring_desc); retire<28, LAG>(sb, lane);
    issue_tile<29, 80, 4, 0, false>(acc1, A, sb, ring_desc); retire<29, LAG>(sb, lane);
    issue_tile<30, 96, 4, 0, false>(acc1, A, sb, ring_desc); retire<30, LAG>(sb, lane);
    issue_tile<31, 112, 4, 0, false>(acc1, A, sb, ring_desc); retire<31, LAG>(sb, lane);
    WSTAMP(28);

    uint32_t thr16 = p * 8192 + tw * 16;
    asm volatile("" : "+r"(thr16));
    issue_tile<32, 0, 4, 1, false>(acc0, A, sb, ring_desc); retire<32, LAG>(sb, lane);
    issue_tile<33, 16, 4, 0, false>(acc0, A, sb, ring_desc); retire<33, LAG>(sb, lane);
    issue_tile<34, 32, 4, 0, false>(acc0, A, sb, ring_desc);
    issue_tile<35, 48, 4, 0, false>(acc0, A, sb, ring_desc);
    fence_acc(acc1);
    mbar_spin_cluster(sb + OFF_BAR + B_PEERX * 8, 0);
    {
      const float r0 = lds32f(rs_addr), r1 = lds32f(rs_addr + 64);
#pragma unroll
      for (int g = 0; g < 4; g++) {
        uint32_t p0, p1, p2, p3;
        epi16s<true>(acc1, g, r0, r1, p0, p1, p2, p3);
        sts128(sb + OFF_U + 3 * 16384 + thr16 + g * 2048, p0, p1, p2, p3);
        st_async4(peer_sb + OFF_U + 5 * 16384 + thr16 + g * 2048, peer_sb + OFF_BAR + (B_LAND + 2 + p) * 8, p0, p1, p2, p3);
      }
    }
    wg_wait<2>(); release_tile<33>(sb, lane);
    issue_tile<36, 64, 4, 0, false>(acc0, A, sb, ring_desc); retire<36, LAG>(sb, lane);
    issue_tile<37, 80, 4, 0, false>(acc0, A, sb, ring_desc); retire<37, LAG>(sb, lane);
    issue_tile<38, 96, 4, 0, false>(acc0, A, sb, ring_desc); retire<38, LAG>(sb, lane);
    issue_tile<39, 112, 4, 0, false>(acc0, A, sb, ring_desc); retire<39, LAG>(sb, lane);
    WSTAMP(21);

    wg_wait<0>();
    release_tile<39>(sb, lane);
    if (lane == 0) mbar_arrive_remote(peer_sb + OFF_BAR + B_PEERX2 * 8);
    if (wq == 0) mbar_spin(sb + OFF_BAR + B_HALO * 8, 0);
    WSTAMP(34);
    {
        const uint32_t Qt = sb + OFF_U, Kt = sb + OFF_U + 16384, Vt = sb + OFF_U + 32768;
        const uint32_t Hk = sb + OFF_HALO, Hv = sb + OFF_HALO + 2048;
        const int g = lane >> 2;
        const uint32_t r0 = 64 * p + 16 * wq;
        const bool halo = (wq == 0);
        const bool first = halo && (ti == 0);
        const int m = lane >> 3, rr = lane & 7;
        const uint32_t kA = ((m < 2 && halo) ? (Hk + p * 1024 + rr * 128) : (Kt + (r0 - 8 + 8 * (m >> 1) + rr) * 128)) + (((m & 1) ^ rr) << 4);
        const uint32_t kB = Kt + (r0 + 8 + rr) * 128 + (((m & 1) ^ rr) << 4);
        const uint32_t vA = (((m & 1) == 0 && halo) ? (Hv + p * 1024 + rr * 128) : (Vt + (r0 - 8 + 8 * (m & 1) + rr) * 128)) + (((m >> 1) ^ rr) << 4);
        const uint32_t vB = Vt + (r0 + 8 + rr) * 128 + (((m & 1) ^ rr) << 4);
        const uint32_t qA = Qt + (r0 + (lane & 15)) * 128 + (((lane >> 4) ^ rr) << 4);
        const bool u0 = (2 * q) <= g, u1 = (2 * q + 1) <= g;
        constexpr float LOG2E = 1.4426950408889634f;
        constexpr uint32_t ONES = 0x3F803F80u;
#pragma unroll 1
        for (int hp = 0; hp < 2; hp++) {
          const uint32_t hx = hp << 6;
          float a0[2], a1[2], b0[2], b1[2];
          uint32_t fv[2][6];
          {
            uint32_t fq[2][4], fk[2][6];
#pragma unroll
            for (int h = 0; h < 2; h++) {
              ldsm4((qA ^ hx) ^ (h << 5), fq[h][0], fq[h][1], fq[h][2], fq[h][3]);
              ldsm4((kA ^ hx) ^ (h << 5), fk[h][0], fk[h][1], fk[h][2], fk[h][3]);
              ldsm2((kB ^ hx) ^ (h << 5), fk[h][4], fk[h][5]);
            }
#pragma unroll
            for (int h = 0; h < 2; h++) {
              float s0[4] = {0.f, 0.f, 0.f, 0.f}, s1[4] = {0.f, 0.f, 0.f, 0.f}, s2[4] = {0.f, 0.f, 0.f, 0.f};
              mma16816(s0, fq[h][0], fq[h][1], fq[h][2], fq[h][3], fk[h][0], fk[h][1]);
              mma16816(s1, fq[h][0], fq[h][1], fq[h][2], fq[h][3], fk[h][2], fk[h][3]);
              mma16816(s2, fq[h][0], fq[h][1], fq[h][2], fq[h][3], fk[h][4], fk[h][5]);
              a0[h] = u0 ? s1[0] : (first ? -INFINITY : s0[0]);
              a1[h] = u1 ? s1[1] : (first ? -INFINITY : s0[1]);
              b0[h] = u0 ? s2[2] : s1[2];
              b1[h] = u1 ? s2[3] : s1[3];
            }
          }
#pragma unroll
          for (int h = 0; h < 2; h++) {
            ldsm4t((vA ^ hx) ^ (h << 5), fv[h][0], fv[h][1], fv[h][2], fv[h][3]);
            ldsm2t((vB ^ hx) ^ (h << 5), fv[h][4], fv[h][5]);
          }
          float ma[2], mb[2];
#pragma unroll
          for (int h = 0; h < 2; h++) { ma[h] = fmaxf(a0[h], a1[h]); mb[h] = fmaxf(b0[h], b1[h]); }
#pragma unroll
          for (int x = 1; x <= 2; x <<= 1) {
            float ta_[2], tb_[2];
#pragma unroll
            for (int h = 0; h < 2; h++) { ta_[h] = __shfl_xor_sync(0xffffffffu, ma[h], x); tb_[h] = __shfl_xor_sync(0xffffffffu, mb[h], x); }
#pragma unroll
            for (int h = 0; h < 2; h++) { ma[h] = fmaxf(ma[h], ta_[h]); mb[h] = fmaxf(mb[h], tb_[h]); }
          }
#pragma unroll
          for (int h = 0; h < 2; h++) {
            const float ea0 = ex2((a0[h] - ma[h]) * LOG2E), ea1 = ex2((a1[h] - ma[h]) * LOG2E);
            const float eb0 = ex2((b0[h] - mb[h]) * LOG2E), eb1 = ex2((b1[h] - mb[h]) * LOG2E);
            const uint32_t P0 = pack_bf16(u0 ? 0.f : ea0, u1 ? 0.f : ea1);
            const uint32_t P2 = pack_bf16(u0 ? ea0 : 0.f, u1 ? ea1 : 0.f);
            const uint32_t P3 = pack_bf16(u0 ? 0.f : eb0, u1 ? 0.f : eb1);
            const uint32_t P5 = pack_bf16(u0 ? eb0 : 0.f, u1 ? eb1 : 0.f);
            float o0[4] = {0.f, 0.f, 0.f, 0.f}, o1[4] = {0.f, 0.f, 0.f, 0.f}, rs[4] = {0.f, 0.f, 0.f, 0.f};
            mma16816(rs, P0, 0u, P2, P3, ONES, ONES);
            mma16816(o0, P0, 0u, P2, P3, fv[h][0], fv[h][1]);
            mma16816(o1, P0, 0u, P2, P3, fv[h][2], fv[h][3]);
            mma1688(rs, 0u, P5, ONES);
            mma1688(o0, 0u, P5, fv[h][4]);
            mma1688(o1, 0u, P5, fv[h][5]);
            const float ia = __fdividef(1.f, rs[0]), ib = __fdividef(1.f, rs[2]);
            stsm4((qA ^ hx) ^ (h << 5), pack_bf16(o0[0] * ia, o0[1] * ia), pack_bf16(o0[2] * ib, o0[3] * ib),
                  pack_bf16(o1[0] * ia, o1[1] * ia), pack_bf16(o1[2] * ib, o1[3] * ib));
          }
        }
    }
    __syncwarp();
    if (lane == 0) mbar_arrive(sb + OFF_BAR + B_O * 8);
    WSTAMP(35);

        if (p == 1) mbar_spin(sb + OFF_BAR + (B_LAG + 1) * 8, 0);
#pragma unroll
    for (int i = 24; i < 32; i++) asm volatile("" : "=f"(acc1[i]));
    issue_tile<40, 0, 4, 2, true>(acc1, A, sb, ring_desc);
    issue_tile<41, 16, 4, 0, true>(acc1, A, sb, ring_desc);
    issue_tile<42, 32, 4, 0, true>(acc1, A, sb, ring_desc);
    if (p == 0 && lane == 0) mbar_arrive(sb + OFF_BAR + (B_LAG + 1) * 8);
    retire<42, LAG>(sb, lane);
    mbar_spin_cluster(sb + OFF_BAR + B_PEERX2 * 8, 0);
#pragma unroll
    for (int g = 0; g < 4; g++) {
      ldsm4(frag_addr<0>(frag0, g), A[4 * g], A[4 * g + 1], A[4 * g + 2], A[4 * g + 3]);
      st_async4(peer_sb + OFF_U + 4 * 16384 + thr16 + g * 2048, peer_sb + OFF_BAR + (B_LAND + 0 + p) * 8, A[4 * g], A[4 * g + 1], A[4 * g + 2], A[4 * g + 3]);
    }
    issue_tile<43, 48, 4, 0, true>(acc1, A, sb, ring_desc); retire<43, LAG>(sb, lane);
#pragma unroll
    for (int g = 0; g < 4; g++) lds128(sb + OFF_U + 3 * 16384 + thr16 + g * 2048, A[16 + 4 * g], A[17 + 4 * g], A[18 + 4 * g], A[19 + 4 * g]);
    __syncwarp();
    if (lane == 0) mbar_arrive(sb + OFF_BAR + B_U03 * 8);
    issue_tile<44, 64, 4, 0, true>(acc1, A, sb, ring_desc); retire<44, LAG>(sb, lane);
    fence_acc(acc0);
    const float f1r0 = lds32f(rs_addr), f1r1 = lds32f(rs_addr + 64);
#pragma unroll
    for (int g = 0; g < 4; g++) {
      epi16s<true>(acc0, g, f1r0, f1r1, A[32 + 4 * g], A[33 + 4 * g], A[34 + 4 * g], A[35 + 4 * g]);
      st_async4(peer_sb + OFF_U + 6 * 16384 + thr16 + g * 2048, peer_sb + OFF_BAR + (B_LAND + 4 + p) * 8, A[32 + 4 * g], A[33 + 4 * g], A[34 + 4 * g], A[35 + 4 * g]);
    }
    issue_tile<45, 80, 4, 0, true>(acc1, A, sb, ring_desc); retire<45, LAG>(sb, lane);
    mbar_spin_cluster(sb + OFF_BAR + (B_LAND + 0 + p) * 8, 0);
#pragma unroll
    for (int g = 0; g < 4; g++) lds128(sb + OFF_U + 4 * 16384 + thr16 + g * 2048, A[48 + 4 * g], A[49 + 4 * g], A[50 + 4 * g], A[51 + 4 * g]);
    issue_tile<46, 96, 4, 0, true>(acc1, A, sb, ring_desc); retire<46, LAG>(sb, lane);
    mbar_spin_cluster(sb + OFF_BAR + (B_LAND + 2 + p) * 8, 0);
#pragma unroll
    for (int g = 0; g < 4; g++) lds128(sb + OFF_U + 5 * 16384 + thr16 + g * 2048, A[64 + 4 * g], A[65 + 4 * g], A[66 + 4 * g], A[67 + 4 * g]);
    issue_tile<47, 112, 4, 0, true>(acc1, A, sb, ring_desc); retire<47, LAG>(sb, lane);
    WSTAMP(22);

    issue_tile<48, 0, 4, 1, false>(acc0, A, sb, ring_desc); retire<48, LAG>(sb, lane);
    issue_tile<49, 48, 4, 0, false>(acc0, A, sb, ring_desc); retire<49, LAG>(sb, lane);
    fence_acc48(acc1);
    const float f2r0 = lds32f(rs_addr), f2r1 = lds32f(rs_addr + 64);
#pragma unroll
    for (int g = 0; g < 3; g++) {
      epi16s<true>(acc1, g, f2r0, f2r1, A[96 + 4 * g], A[97 + 4 * g], A[98 + 4 * g], A[99 + 4 * g]);
      st_async4(peer_sb + OFF_U + 7 * 16384 + thr16 + g * 2048, peer_sb + OFF_BAR + (B_LAND + 6 + p) * 8, A[96 + 4 * g], A[97 + 4 * g], A[98 + 4 * g], A[99 + 4 * g]);
    }
    issue_tile<50, 16, 4, 0, false>(acc0, A, sb, ring_desc); retire<50, LAG>(sb, lane);
    mbar_spin_cluster(sb + OFF_BAR + (B_LAND + 4 + p) * 8, 0);
#pragma unroll
    for (int g = 0; g < 4; g++) lds128(sb + OFF_U + 6 * 16384 + thr16 + g * 2048, A[80 + 4 * g], A[81 + 4 * g], A[82 + 4 * g], A[83 + 4 * g]);
    issue_tile<51, 32, 4, 0, false>(acc0, A, sb, ring_desc); retire<51, LAG>(sb, lane);
    issue_tile<52, 64, 4, 0, false>(acc0, A, sb, ring_desc); retire<52, LAG>(sb, lane);
    issue_tile<53, 80, 4, 0, false>(acc0, A, sb, ring_desc); retire<53, LAG>(sb, lane);
    mbar_spin_cluster(sb + OFF_BAR + (B_LAND + 6 + p) * 8, 0);
#pragma unroll
    for (int g = 0; g < 3; g++) lds128(sb + OFF_U + 7 * 16384 + thr16 + g * 2048, A[112 + 4 * g], A[113 + 4 * g], A[114 + 4 * g], A[115 + 4 * g]);
    __syncwarp();
    if (lane == 0) mbar_arrive(sb + OFF_BAR + B_LF * 8);
    issue_tile<54, 96, 3, 0, false>(acc0, A, sb, ring_desc); retire<54, LAG>(sb, lane);
    issue_tile<55, 112, 3, 0, false>(acc0, A, sb, ring_desc); retire<55, LAG>(sb, lane);
    WSTAMP(23);

    auto store_partial = [&](float (&acc)[32], int blk) {
      fence_acc(acc);
      const int c = (ta + 1 + blk) & 3;
      const uint32_t tg = (lds32(sb + OFF_TAG) & 1u) << 16;
      uint32_t twl = tw;
      asm volatile("" : "+r"(twl));
      uint4* dst = &g_part[(((((ti * 2 + tb) * 4 + c) * 4 + ta) * 2 + p) * 512) + twl];
      auto tagged = [&](float lo, float hi) { return pack_bf16(lo, __uint_as_float((__float_as_uint(hi) + 0x10000u) & 0xfffe0000u)) | tg; };
#pragma unroll
      for (int v = 0; v < 4; v++)
        stg_relaxed(dst + v * 128, tagged(acc[8 * v], acc[8 * v + 1]), tagged(acc[8 * v + 2], acc[8 * v + 3]),
                    tagged(acc[8 * v + 4], acc[8 * v + 5]), tagged(acc[8 * v + 6], acc[8 * v + 7]));
    };
    issue_tile<56, 0, 4, 1, false>(acc1, A, sb, ring_desc); retire<56, LAG>(sb, lane);
    issue_tile<57, 48, 4, 0, false>(acc1, A, sb, ring_desc); retire<57, LAG>(sb, lane);
    issue_tile<58, 16, 4, 0, false>(acc1, A, sb, ring_desc);
    issue_tile<59, 32, 4, 0, false>(acc1, A, sb, ring_desc);
    store_partial(acc0, 0);
    wg_wait<2>(); release_tile<57>(sb, lane);
    issue_tile<60, 64, 4, 0, false>(acc1, A, sb, ring_desc); retire<60, LAG>(sb, lane);
    issue_tile<61, 80, 4, 0, false>(acc1, A, sb, ring_desc); retire<61, LAG>(sb, lane);
    issue_tile<62, 96, 3, 0, false>(acc1, A, sb, ring_desc); retire<62, LAG>(sb, lane);
    issue_tile<63, 112, 3, 0, false>(acc1, A, sb, ring_desc); retire<63, LAG>(sb, lane);
    WSTAMP(29);
    uint32_t pa[16];
    auto part_src = [&](int s) {
      uint32_t twl = tw;
      asm volatile("" : "+r"(twl));
      return (const uint4*)&g_part[(((((ti * 2 + tb) * 4 + ta) * 4 + ((ta + 3 - s) & 3)) * 2 + p) * 512) + twl];
    };
    auto add_partial = [&](float (&dst)[32], int s, bool overwrite) {
      ensure_tagged<128, 0x10000u>(pa, part_src(s), (lds32(sb + OFF_TAG) & 1u) << 16);
#pragma unroll
      for (int e = 0; e < 16; e++) {
        if (overwrite) { set_lo(dst[2 * e], pa[e]); set_hi<0xfffe0000u>(dst[2 * e + 1], pa[e]); }
        else { acc_add(dst[2 * e], bf_lo(pa[e])); acc_add(dst[2 * e + 1], __uint_as_float(pa[e] & 0xfffe0000u)); }
      }
    };
    issue_tile<64, 0, 4, 1, false>(acc0, A, sb, ring_desc); retire<64, LAG>(sb, lane);
    issue_tile<65, 48, 4, 0, false>(acc0, A, sb, ring_desc); retire<65, LAG>(sb, lane);
    issue_tile<66, 16, 4, 0, false>(acc0, A, sb, ring_desc);
    issue_tile<67, 32, 4, 0, false>(acc0, A, sb, ring_desc);
    store_partial(acc1, 1);
    ldg4_relaxed<128>(pa, part_src(0));
    wg_wait<2>(); release_tile<65>(sb, lane);
    issue_tile<68, 64, 4, 0, false>(acc0, A, sb, ring_desc);
    issue_tile<69, 80, 4, 0, false>(acc0, A, sb, ring_desc);
    mbar_spin(sb + OFF_BAR + (B_RES + p) * 8, 0);
#pragma unroll
    for (int g = 0; g < 4; g++) {
      uint32_t r0, r1, r2, r3;
      ldsm4(frag_addr<7 * 16384>(frag0, g), r0, r1, r2, r3);
      set_lo(acc1[8 * g + 0], r0); set_hi<0xffff0000u>(acc1[8 * g + 1], r0); set_lo(acc1[8 * g + 2], r1); set_hi<0xffff0000u>(acc1[8 * g + 3], r1);
      set_lo(acc1[8 * g + 4], r2); set_hi<0xffff0000u>(acc1[8 * g + 5], r2); set_lo(acc1[8 * g + 6], r3); set_hi<0xffff0000u>(acc1[8 * g + 7], r3);
    }
    wg_wait<2>(); release_tile<67>(sb, lane);
    issue_tile<70, 96, 3, 0, false>(acc0, A, sb, ring_desc);
    issue_tile<71, 112, 3, 0, false>(acc0, A, sb, ring_desc);
    wg_wait<2>(); release_tile<69>(sb, lane);
    add_partial(acc1, 0, false);
    ldg4_relaxed<128>(pa, part_src(1));
    WSTAMP(30);

    issue_tile<72, 0, 4, 0, false>(acc1, A, sb, ring_desc);
    wg_wait<1>();
    store_partial(acc0, 2);
    WSTAMP(40);
    issue_tile<73, 48, 4, 0, false>(acc1, A, sb, ring_desc);
    issue_tile<74, 16, 4, 0, false>(acc1, A, sb, ring_desc);
    issue_tile<75, 32, 4, 0, false>(acc1, A, sb, ring_desc);
    issue_tile<76, 64, 4, 0, false>(acc1, A, sb, ring_desc);
    add_partial(acc0, 1, true);
    issue_tile<77, 80, 4, 0, false>(acc1, A, sb, ring_desc);
    ldg4_relaxed<128>(pa, part_src(2));
    issue_tile<78, 96, 3, 0, false>(acc1, A, sb, ring_desc);
    issue_tile<79, 112, 3, 0, false>(acc1, A, sb, ring_desc);
    WSTAMP(24);
    add_partial(acc0, 2, false);
    WSTAMP(25);
    wg_wait<0>();
    fence_acc(acc1);
    WSTAMP(39);
#pragma unroll
    for (int v = 0; v < 4; v++)
      stsm4(frag_addr<3 * 16384>(frag0, v), pack_bf16(acc1[8 * v] + acc0[8 * v], acc1[8 * v + 1] + acc0[8 * v + 1]),
            pack_bf16(acc1[8 * v + 2] + acc0[8 * v + 2], acc1[8 * v + 3] + acc0[8 * v + 3]),
            pack_bf16(acc1[8 * v + 4] + acc0[8 * v + 4], acc1[8 * v + 5] + acc0[8 * v + 5]),
            pack_bf16(acc1[8 * v + 6] + acc0[8 * v + 6], acc1[8 * v + 7] + acc0[8 * v + 7]));
    __syncwarp();
    WSTAMP(38);
    {
      uint32_t ll = lane;
      asm volatile("" : "+r"(ll));
      uint8_t* outp = reinterpret_cast<uint8_t*>(prm.out) + (size_t)(2 * (64 * ti + 16 * wq + (ll >> 3)) + p) * 1024 + (256 * tb + 64 * ta) * 2 + (ll & 7) * 16;
#pragma unroll
      for (int it = 0; it < 4; it++) {
        const int r = 4 * it + (lane >> 3);
        uint32_t v0, v1, v2, v3;
        lds128(sb + OFF_U + 3 * 16384 + p * 8192 + wq * 2048 + r * 128 + (((lane & 7) ^ (r & 7)) << 4), v0, v1, v2, v3);
        *reinterpret_cast<uint4*>(outp + (size_t)it * 8 * 1024) = make_uint4(v0, v1, v2, v3);
      }
    }
    if (lane == 0) mbar_arrive(sb + OFF_BAR + B_DONE * 8);
    if (warp == 0) { TSTAMP(26); GSTAMP(61); }
  }
}

typedef CUresult (*EncodeFn)(CUtensorMap*, CUtensorMapDataType, cuuint32_t, void*, const cuuint64_t*, const cuuint64_t*,
                             const cuuint32_t*, const cuuint32_t*, CUtensorMapInterleave, CUtensorMapSwizzle,
                             CUtensorMapL2promotion, CUtensorMapFloatOOBfill);

CUtensorMap make_map(EncodeFn fn, const void* ptr, uint64_t rows, uint64_t cols) {
  CUtensorMap m;
  cuuint64_t dims[2] = {cols, rows};
  cuuint64_t strides[1] = {cols * 2};
  cuuint32_t box[2] = {64, 64};
  cuuint32_t es[2] = {1, 1};
  fn(&m, CU_TENSOR_MAP_DATA_TYPE_BFLOAT16, 2, const_cast<void*>(ptr), dims, strides, box, es, CU_TENSOR_MAP_INTERLEAVE_NONE,
     CU_TENSOR_MAP_SWIZZLE_128B, CU_TENSOR_MAP_L2_PROMOTION_L2_128B, CU_TENSOR_MAP_FLOAT_OOB_FILL_NONE);
  return m;
}

}

extern "C" void kernel_launch(void* const* d_in, const int* in_sizes, int n_in, void* d_out, int out_size) {
  (void)in_sizes; (void)n_in; (void)out_size;
  const __nv_bfloat16* x = (const __nv_bfloat16*)d_in[0];
  const __nv_bfloat16* wqkv = (const __nv_bfloat16*)d_in[1];
  const __nv_bfloat16* wo = (const __nv_bfloat16*)d_in[2];
  const __nv_bfloat16* w1 = (const __nv_bfloat16*)d_in[4];
  const __nv_bfloat16* w2 = (const __nv_bfloat16*)d_in[5];

  static EncodeFn encode = nullptr;
  if (!encode) {
    void* fn = nullptr;
    cudaDriverEntryPointQueryResult qr;
    cudaGetDriverEntryPoint("cuTensorMapEncodeTiled", &fn, cudaEnableDefault, &qr);
    encode = (EncodeFn)fn;
    cudaFuncSetAttribute(fused_kernel, cudaFuncAttributeMaxDynamicSharedMemorySize, SMEM_BYTES);
  }
  const CUtensorMap tmX = make_map(encode, x, 1024, 1024);
  const CUtensorMap tmWqkv = make_map(encode, wqkv, 512, 1536);
  const CUtensorMap tmW1 = make_map(encode, w1, 512, kF);
  const CUtensorMap tmWo = make_map(encode, wo, 512, 512);
  const CUtensorMap tmW2 = make_map(encode, w2, kF, 512);
  Params prm{x, (__nv_bfloat16*)d_out, DESC_CONST};

  cudaLaunchConfig_t cfg = {};
  cfg.gridDim = dim3(128);
  cfg.blockDim = dim3(384);
  cfg.dynamicSmemBytes = SMEM_BYTES;
  cfg.stream = cudaStreamPerThread;
  cudaLaunchAttribute at[1];
  at[0].id = cudaLaunchAttributeClusterDimension;
  at[0].val.clusterDim.x = 2; at[0].val.clusterDim.y = 1; at[0].val.clusterDim.z = 1;
  cfg.attrs = at; cfg.numAttrs = 1;
  cudaLaunchKernelEx(&cfg, fused_kernel, tmX, tmWqkv, tmW1, tmWo, tmW2, prm);
}
```
